```python
import torch

def _softmax(x, axis=-1):
    return torch.softmax(x, dim=axis)
def _gelu(x):
    return torch.nn.functional.gelu(x, approximate="tanh")
def _silu(x):
    return torch.nn.functional.silu(x)
def _sigmoid(x):
    return torch.sigmoid(x)
def _layernorm(x, axis=-1, eps=1e-5):
    m = x.mean(dim=axis, keepdim=True)
    v = x.var(dim=axis, keepdim=True, unbiased=False)
    return (x - m) / torch.sqrt(v + eps)
def _scatter_add(tgt, idx, src, axis=0):
    return tgt.clone().index_add_(axis, idx, src)
def _segment_sum(src, seg, n):
    out = torch.zeros((n,) + src.shape[1:], dtype=src.dtype)
    return out.index_add_(0, seg, src)
def _pad(x, pw):
    flat = tuple(v for pair in reversed(pw) for v in pair)
    return torch.nn.functional.pad(x, flat)

kernel_name = 'recurrent_scan__spectral_gfnet__mixer_s_mlp__prompt'

def setup_inputs():

    _w = (lambda a: (lambda t: t.to(torch.bfloat16) if t.is_floating_point() else t)(torch.as_tensor(a)))
    def _A_setup():
        B, S, D = 1, 2048, 640
        Df = D // 2 + 1
        return {
            "x": _w((lambda *s: torch.randn(*s, dtype=torch.bfloat16) * 0.05)(B, S, D)),
            "w_r": _w((lambda *s: torch.randn(*s, dtype=torch.bfloat16) * 0.2)(S, Df) * 0.02),
            "w_i": _w((lambda *s: torch.randn(*s, dtype=torch.bfloat16) * 0.2)(S, Df) * 0.02),
        }
    _A_in = _A_setup()

    def _B_setup():
        B, S, D, F = 1, 2048, 640, 1536
        return {
            "x":  _w((lambda *s: torch.randn(*s, dtype=torch.bfloat16) * 0.05)(B, S, D)),
            "w1": _w((lambda *s: torch.randn(*s, dtype=torch.bfloat16) * 1.6)(D, D) * (D ** -0.5)),
            "w2": _w((lambda *s: torch.randn(*s, dtype=torch.bfloat16) * 1.6)(D, D) * (D ** -0.5)),
            "w3": _w((lambda *s: torch.randn(*s, dtype=torch.bfloat16) * 1.6)(D, F) * (D ** -0.5)),
            "w4": _w((lambda *s: torch.randn(*s, dtype=torch.bfloat16) * 1.6)(F, D) * (F ** -0.5)),
        }
    _B_in = _B_setup()

    return {
        "A_x": _A_in["x"],
        "A_w_r": _A_in["w_r"],
        "A_w_i": _A_in["w_i"],
        "B_x": _B_in["x"],
        "B_w1": _B_in["w1"],
        "B_w2": _B_in["w2"],
        "B_w3": _B_in["w3"],
        "B_w4": _B_in["w4"],
    }

def reference(A_x, A_w_r, A_w_i, B_x, B_w1, B_w2, B_w3, B_w4):
    def _A_ref(x, w_r, w_i):
        B, S, D = x.shape
        X = (lambda x, axes=(-2,-1): torch.fft.rfft2(x.float(), dim=axes))(x, axes=(-2, -1))
        W = w_r + 1j * w_i
        X = X * W
        y = (lambda x, s, axes=(-2,-1): torch.fft.irfft2(x, s=s, dim=axes).to(torch.bfloat16))(X, (S, D), axes=(-2, -1))
        return y

    def _B_ref(x, w1, w2, w3, w4):
        B, S, D = x.shape
        h = _gelu(_layernorm(x, axis=-1) @ w1)
        c = D // 4
        g0 = _pad(h[:, :, 0*c:1*c], ((0, 0), (1, 0), (0, 0)))[:, :S, :]
        g1 = _pad(h[:, :, 1*c:2*c], ((0, 0), (0, 1), (0, 0)))[:, 1:, :]
        g2 = _pad(h[:, :, 2*c:3*c], ((0, 0), (2, 0), (0, 0)))[:, :S, :]
        g3 = _pad(h[:, :, 3*c:   ], ((0, 0), (0, 2), (0, 0)))[:, 2:, :]
        hs = torch.concatenate([g0, g1, g2, g3], axis=-1) @ w2
        x1 = x + hs
        h2 = _gelu(_layernorm(x1, axis=-1) @ w3) @ w4
        return x1 + h2

    x = A_x
    xn = _layernorm(x, axis=-1)
    s = _A_ref(xn, A_w_r, A_w_i)
    g = _silu(_B_ref(xn, B_w1, B_w2, B_w3, B_w4))
    return x + s * g
```

```cpp
#include <cuda_runtime.h>
#include <cuda_bf16.h>
#include <cuda.h>
#include <stdint.h>

typedef __nv_bfloat16 bf16;

constexpr int ROW_H = 2, ROW_X1 = ROW_H + 2048, ROWS_SC = ROW_X1 + 2048 + 32;
__device__ __align__(1024) bf16 g_sc[ROWS_SC * 640];
__device__ __align__(1024) bf16 g_h2[2048 * 1536];
__device__ __align__(1024) bf16 g_UV[2 * 640 * 2048];
constexpr int WT_LD = 2048 + 32;
__device__ __align__(1024) uint32_t g_Wt[344 * WT_LD];
__device__ __align__(1024) bf16 g_w4t[640 * 1536];
struct Small {
  unsigned cnt[128 * 32];
  float4 rowstat[2048];
  float4 x1part[5 * 2048];
  float4 cs3[5 * 768];
};
__device__ __align__(1024) Small g_small;

enum { C_EPOCH = 0, C_U = 1  , C_V = 2, C_H = 36, C_X1 = 62, C_H2 = 88 };
enum { N_EPOCH = 132, N_U = 256, N_V = 132, N_H = 5, N_X1 = 5, N_H2 = 8 };

enum { L_X80 = 0, L_W1, L_X128, L_W2, L_W3, L_SC80, L_SC128, L_H2, L_V, L_T, L_W4T, M_HST, M_X1ST, L_XT, M_H2H,
       L_W4, M_W4T, L_WR, L_WI, M_WT, M_UST, R_U, R_WT, L_U, M_VST, R_V, L_XF, L_X1F, M_OUT, M_COUNT };

#define TAB2 1
struct OpTab { uint32_t v[2 * 80]; };
struct Params {
  const bf16 *x, *w1;
  Small* sm;
  const bf16 *wr, *wi, *w2, *w3, *w4, *dft;
  const char* fft;
  const uint32_t* Wt;
  OpTab ops;
  CUtensorMap m[M_COUNT];
};

#define STAMP2(k, i) do { } while (0)
#define STAMP(i) do { } while (0)

constexpr uint32_t SB = 1024;
constexpr uint32_t SLOT = 26624, QSLOT = 40960;
constexpr uint32_t G1SLOT = SLOT + 1024;
constexpr uint32_t O_STG = 2 * QSLOT;
constexpr uint32_t O_XT = 3 * G1SLOT;
constexpr uint32_t O_M32 = 2 * SLOT, O_C = O_M32 + 8192;
constexpr uint32_t O_FD = 3 * SLOT, O_FAC = 4 * SLOT;
constexpr uint32_t O_X1S = 163840;
constexpr uint32_t O_WORK = 186368;
constexpr uint32_t O_W4B = O_WORK, O_XS = O_WORK + 8192;
constexpr uint32_t O_STG3 = 169984;
constexpr uint32_t O_MISC = O_WORK + 32768;
constexpr uint32_t E_NONE = 82;
constexpr uint32_t O_FULL = O_MISC, O_EMPTY = O_FULL + 8 * 88, O_BAR = O_EMPTY + 8 * 88;
constexpr uint32_t O_EP = O_BAR + 8 * 34;
constexpr uint32_t O_RM = O_EP + 32;
constexpr uint32_t O_AB1 = O_RM + 640;
constexpr uint32_t O_R1F = O_AB1 + 640;
constexpr uint32_t O_RED = O_R1F + 512;
constexpr uint32_t O_AB3 = O_RED + 1024;
constexpr uint32_t O_CS3 = O_AB3 + 1024;
constexpr uint32_t O_RB = (O_CS3 + 768 + 127) / 128 * 128;
constexpr uint32_t SMEM_BYTES = O_RB + 5376;
static_assert(O_RM % 16 == 0 && SMEM_BYTES <= 232448, "smem map");
enum { B_STAT3 = 0, B_STAT1, B_MAT, B_WLD, B_W4LD, B_EP, B_PUB1, B_PUB2, B_PUB3, B_X1ST, B_WTST, B_WOK, B_VOK, B_FAC, B_RB, B_UW, B_XSD, B_W4W, B_WTW, B_VW  ,
       B_HW = B_VW + 3  , B_X1W = B_HW + 2, B_H2W  , B_H2A = B_H2W + 3  , B_COUNT = B_H2A + 2, B_XS = B_COUNT };

constexpr OpTab make_ops() {
  OpTab t{};
  for (int op = 7; op < 78; op++) {
    uint32_t dst = 0, pred = E_NONE;
    if (op < 32) {
      if (op < 10) { dst = (op - 7) * G1SLOT; pred = op - 7; }
      else if (op < 17) { dst = ((op - 7) % 7) * SLOT; pred = op - 7; }
      else if (op < 22) { dst = (op == 17 ? 3 : op - 18) * SLOT; pred = op == 17 ? 22 : op + 8; }
      else { const int k = op - 22; dst = (k < 7 ? (k + 3) % 7 : k - 3) * SLOT; pred = k < 7 ? 10 + k : op - 6; }
    } else if (op < 43) { const int k = op - 33; dst = ((k + 3) & 3) * QSLOT; pred = k == 0 ? 31 : (k == 1 && !TAB2) ? 19 : k < 4 ? 20 : op - 4; }
    else {
      const int k = op - 44;
      dst = ((k + 5) % 7) * SLOT;
      pred = k == 0 ? 41 : k == 1 ? 43 : k < 4 ? 42 : k < 7 ? 83 : op - 7;
    }
    const uint32_t bar = SB + O_EMPTY + 8 * pred - O_MISC;
    t.v[op] = (SB + dst + (op < 32 ? 0 : 16384)) | ((TAB2 && op == 35 ? SB + O_FULL + 8 * 33 - O_MISC : bar) << 18);
    t.v[80 + op] = (SB + dst + (op < 32 ? 16384 : 0)) | (bar << 18);
  }
  return t;
}

__host__ __device__ constexpr int gpc_pos(int smid) {
  const int t = smid >> 1;
  const int g = t < 32 ? (t & 7) : t < 60 ? 1 + (t - 32) % 7 : t < 62 ? t - 54 : 0;
  const int p = t < 32 ? (t >> 3) : t < 60 ? 4 + (t - 32) / 7 : t < 62 ? 8 : t - 58;
  return 32 * g + 2 * p + (smid & 1);
}
__host__ __device__ constexpr int rank_a(int gp) {
  return (gp & 31) == 17 ? 124 + (gp >> 5) : 16 * (gp >> 5) + (gp & 31) + ((gp >> 5) == 7 ? 1 : 0);
}
#define RB_OF(r) (((r) >> 5) * 4 + (((r) >> 2) & 3))
#define CB_OF(r) ((((r) >> 4) & 1) * 4 + ((r) & 3))
__host__ __device__ constexpr int rank_b(int gp) {
  return (gp & 31) < 16 ? 16 * ((0x75642310 >> (4 * (gp >> 5))) & 7) + (gp & 31) : 100 + 2 * (gp >> 5) + (gp & 31);
}

struct DftTab { uint16_t v[2 * 640 * 640]; };
struct FftTab { uint16_t m[3 * 4096]; uint32_t tw[2048]; };
#ifdef __CUDA_ARCH__
constexpr double c_cos(int n, int N) {
  n %= N;
  if (2 * n > N) n = N - n;
  double sg = 1;
  if (4 * n > N) { n = N / 2 - n; sg = -1; }
  if (4 * n == N) return 0;
  const double x = n * (6.283185307179586477 / N), x2 = x * x;
  double t = 1, s = 1;
  for (int i = 1; i <= 12; i++) { t *= -x2 / ((2 * i - 1) * (2 * i)); s += t; }
  return sg * s;
}
constexpr uint16_t c_bf16(double v) {
  if (v == 0) return 0;
  const uint16_t sg = v < 0 ? 0x8000 : 0;
  if (v < 0) v = -v;
  int e = 0;
  while (v < 1) { v *= 2; e--; }
  const double m = v * 128;
  int mi = (int)m;
  if (m - mi > 0.5 || (m - mi == 0.5 && (mi & 1))) mi++;
  if (mi == 256) { mi = 128; e++; }
  return sg | ((e + 127) << 7) | (mi - 128);
}
constexpr DftTab make_dft() {
  DftTab t{};
  uint16_t c[640] = {}, cs[640] = {};
  for (int n = 0; n < 640; n++) { c[n] = c_bf16(c_cos(n, 640)); cs[n] = c_bf16(c_cos(n, 640) * (2.0 / (2048.0 * 640.0))); }
  for (int kk = 0; kk < 640; kk++) {
    const int k = (kk >> 1) ? (kk >> 1) : 320;
    int idx = 160 * (kk & 1);
    for (int d = 0; d < 640; d++) {
      t.v[kk * 640 + d] = kk == 1 ? 0 : c[idx];
      t.v[640 * 640 + d * 640 + kk] = kk == 1 ? 0 : kk == 0 ? (uint16_t)(cs[idx] - 0x80) : cs[idx];
      idx += k;
      if (idx >= 640) idx -= 640;
    }
  }
  return t;
}
constexpr FftTab make_fft() {
  FftTab t{};
  for (int mat = 0; mat < 3; mat++)
    for (int row = 0; row < 64; row++)
      for (int j = 0; j < 64; j++) {
        int ph = row * j + (mat == 2 ? 48 : 0);
        if (mat == 0) {
          const int ka = (row >> 4) * 8 + (row & 7), cp = (row >> 3) & 1, c = j >> 5;
          ph = 2 * ka * (j & 31) + (cp == c ? 0 : (cp ? 16 : 48));
        }
        t.m[mat * 4096 + row * 64 + (((j >> 3) ^ (row & 7)) << 3) + (j & 7)] = c_bf16(c_cos(ph, 64));
      }
  for (int ka = 0; ka < 32; ka++)
    for (int n2 = 0; n2 < 64; n2++)
      for (int c = 0; c < 2; c++) t.tw[(((n2 >> 4) * 32 + ka) * 4 + ((n2 >> 1) & 3)) * 4 + ((n2 >> 3) & 1) * 2 + c] |= (uint32_t)c_bf16(c_cos(ka * n2 + 512 * c, 2048)) << (16 * (n2 & 1));
  return t;
}
#define CT_INIT(f) = f()
#else
#define CT_INIT(f)
#endif
__device__ __align__(1024) DftTab g_dft CT_INIT(make_dft);
__device__ __align__(1024) FftTab g_fft CT_INIT(make_fft);

__device__ __forceinline__ void mbar_init(uint32_t bar, uint32_t cnt) {
  asm volatile("mbarrier.init.shared::cta.b64 [%0], %1;" ::"r"(bar), "r"(cnt) : "memory");
}
__device__ __forceinline__ void mbar_expect_tx(uint32_t bar, uint32_t bytes) {
  asm volatile("mbarrier.arrive.expect_tx.shared::cta.b64 _, [%0], %1;" ::"r"(bar), "r"(bytes) : "memory");
}
__device__ __forceinline__ void mbar_arrive(uint32_t bar) {
  asm volatile("mbarrier.arrive.shared::cta.b64 _, [%0];" ::"r"(bar) : "memory");
}
__device__ __forceinline__ void mbar_wait(uint32_t bar, uint32_t parity) {
  asm volatile(
      "{\n.reg .pred p, q;\n.reg .u32 c;\nmov.u32 c, 0;\n"
      "W_LOOP:\nmbarrier.try_wait.parity.shared::cta.b64 p, [%0], %1;\n@p bra.uni W_DONE;\n"
      "add.u32 c, c, 1;\nsetp.lt.u32 q, c, 0x400000;\n@q bra.uni W_LOOP;\ntrap;\nW_DONE:\n}"
      ::"r"(bar), "r"(parity) : "memory");
}
__device__ __forceinline__ bool elect() {
  uint32_t p;
  asm volatile("{\n.reg .pred P;\nelect.sync _|P, 0xffffffff;\nselp.u32 %0, 1, 0, P;\n}" : "=r"(p));
  return p;
}
__device__ __forceinline__ void tma2(uint32_t dst, const CUtensorMap* m, int c0, int c1, uint32_t bar) {
  asm volatile("cp.async.bulk.tensor.2d.shared::cluster.global.mbarrier::complete_tx::bytes [%0], [%1, {%3, %4}], [%2];"
               ::"r"(dst), "l"(m), "r"(bar), "r"(c0), "r"(c1) : "memory");
}
__device__ __forceinline__ void tma3(uint32_t dst, const CUtensorMap* m, int c0, int c1, int c2, uint32_t bar) {
  asm volatile("cp.async.bulk.tensor.3d.shared::cluster.global.mbarrier::complete_tx::bytes [%0], [%1, {%3, %4, %5}], [%2];"
               ::"r"(dst), "l"(m), "r"(bar), "r"(c0), "r"(c1), "r"(c2) : "memory");
}
__device__ __forceinline__ void tma2_st(const CUtensorMap* m, uint32_t src, int c0, int c1) {
  asm volatile("cp.async.bulk.tensor.2d.global.shared::cta.bulk_group [%0, {%2, %3}], [%1];"
               ::"l"(m), "r"(src), "r"(c0), "r"(c1) : "memory");
}
__device__ __forceinline__ void tma3_st(const CUtensorMap* m, uint32_t src, int c0, int c1, int c2) {
  asm volatile("cp.async.bulk.tensor.3d.global.shared::cta.bulk_group [%0, {%2, %3, %4}], [%1];"
               ::"l"(m), "r"(src), "r"(c0), "r"(c1), "r"(c2) : "memory");
}
__device__ __forceinline__ void bulk_ld(uint32_t dst, const void* src, uint32_t bytes, uint32_t bar) {
  asm volatile("cp.async.bulk.shared::cluster.global.mbarrier::complete_tx::bytes [%0], [%1], %2, [%3];"
               ::"r"(dst), "l"(src), "r"(bytes), "r"(bar) : "memory");
}
__device__ __forceinline__ float4 ld_tag(const float4* p) {
  float4 v;
  asm volatile("ld.relaxed.gpu.global.v4.f32 {%0, %1, %2, %3}, [%4];" : "=f"(v.x), "=f"(v.y), "=f"(v.z), "=f"(v.w) : "l"(p) : "memory");
  return v;
}
__device__ __forceinline__ void st_tag(float4* p, float x, float y, float z, unsigned tag) {
  asm volatile("st.relaxed.gpu.global.v4.f32 [%0], {%1, %2, %3, %4};" ::"l"(p), "f"(x), "f"(y), "f"(z), "f"(__uint_as_float(tag)) : "memory");
}
template <int N>
__device__ __forceinline__ float4 gather_tagged(const float4* p, int stride, unsigned tag) {
#pragma unroll 1
  for (int it = 0;; it++) {
    float4 v[N];
#pragma unroll
    for (int j = 0; j < N; j++) v[j] = ld_tag(p + j * stride);
    bool ok = __float_as_uint(v[0].w) == tag;
#pragma unroll
    for (int j = 1; j < N; j++) { ok = ok && __float_as_uint(v[j].w) == tag; v[0].x += v[j].x; v[0].y += v[j].y; }
    if (__all_sync(~0u, ok)) return v[0];
    if (it > (1 << 21)) __trap();
  }
}
__device__ __forceinline__ void l2_prefetch(const void* p) { asm volatile("prefetch.global.L2 [%0];" ::"l"(p) : "memory"); }
#define FFT2_GATE 3
#define XT_OP 3
#define PF0 3
#define W3_LATE 35
#define F1C_GATE (sb + O_BAR + 8 * B_X1ST)
#define V_OP 44
#define W4_OP 9
#define WLD_GATE (sb + O_BAR + 8 * B_PUB2)
#define SP_START 2500
#define SP_GAP 200
#define XS_AFTER 2
#define G1_HOLD 0
#define EARLY_PF 5
#define F1_HOLD 0
#define XT_HOLD 0
#define F1C_D 3
#define V_SH 2
#define X1F_OP 70
#define POLL2 0
#define OPS_WARM 0
#define POLL_LAG 100
#define POLL_STEP 250
#define WT_OP 33
__device__ __forceinline__ void st_commit() { asm volatile("cp.async.bulk.commit_group;" ::: "memory"); }
__device__ __forceinline__ void st_wait_all() { asm volatile("cp.async.bulk.wait_group 0;" ::: "memory"); }
__device__ __forceinline__ void fence_async_smem() { asm volatile("fence.proxy.async.shared::cta;" ::: "memory"); }
__device__ __forceinline__ void fence_async_gmem() { asm volatile("fence.proxy.async.global;" ::: "memory"); }
__device__ __forceinline__ void bar_sync(int id, int n) { asm volatile("bar.sync %0, %1;" ::"r"(id), "r"(n) : "memory"); }
__device__ __forceinline__ void tile_written(uint32_t bar, int lane) {
  fence_async_smem();
  __syncwarp();
  if (lane == 0) mbar_arrive(bar);
}
__device__ __forceinline__ void wg_fence() { asm volatile("wgmma.fence.sync.aligned;" ::: "memory"); }
__device__ __forceinline__ void wg_commit() { asm volatile("wgmma.commit_group.sync.aligned;" ::: "memory"); }
template <int N> __device__ __forceinline__ void wg_wait() { asm volatile("wgmma.wait_group.sync.aligned %0;" ::"n"(N) : "memory"); }
struct Desc {
  uint32_t lo;
  __device__ __forceinline__ Desc operator+(uint32_t o) const { return Desc{lo + o}; }
  __device__ __forceinline__ operator uint64_t() const {
    uint64_t d;
    asm("mov.b64 %0, {%1, %2};" : "=l"(d) : "r"(lo), "r"(0x40000040u));
    return d;
  }
};
__device__ __forceinline__ Desc desc(uint32_t addr, uint32_t lbo) { return Desc{(addr >> 4) | ((lbo >> 4) << 16)}; }
__device__ __forceinline__ void red_relaxed(const Params& P, int c) {
  asm volatile("red.relaxed.gpu.global.add.u32 [%0], %1;" ::"l"(P.sm->cnt + c * 32), "r"(1) : "memory");
}
__device__ __forceinline__ void publish(const Params& P, uint32_t free_bar, int c, int rankB, int sid) {
  const Params& PP = P; (void)PP;
  st_commit();
  st_wait_all();
  mbar_arrive(free_bar);
  STAMP(sid);
  asm volatile("fence.acq_rel.gpu;" ::: "memory");
  red_relaxed(P, c);
  STAMP(sid + 1);
}
__device__ __forceinline__ void poll(const Params& P, int c, int n, unsigned target, int lane) {
  const unsigned* p = P.sm->cnt + (c + min(lane, n - 1)) * 32;
#pragma unroll 1
  for (int it = 0;; it++) {
    unsigned v;
    asm volatile("ld.acquire.gpu.global.u32 %0, [%1];" : "=r"(v) : "l"(p) : "memory");
    if (__all_sync(~0u, (int)(v - target) >= 0)) break;
    if (it > (1 << 21)) __trap();
  }
}
__device__ __forceinline__ uint32_t pack(float lo, float hi) {
  uint32_t r;
  asm("cvt.rn.bf16x2.f32 %0, %1, %2;" : "=r"(r) : "f"(hi), "f"(lo));
  return r;
}
__device__ __forceinline__ float blo(uint32_t v) { return __uint_as_float(v << 16); }
__device__ __forceinline__ float bhi(uint32_t v) { return __uint_as_float(v & 0xffff0000u); }
__device__ __forceinline__ float tanh_fast(float x) { float y; asm("tanh.approx.f32 %0, %1;" : "=f"(y) : "f"(x)); return y; }
__device__ __forceinline__ float gelu_half(float z) {
  float u = z * fmaf(z * z, 8.f * 0.7978845608f * 0.044715f, 2.f * 0.7978845608f);
  return fmaf(z, tanh_fast(u), z);
}
__device__ __forceinline__ void stsm(uint32_t a, uint32_t r0, uint32_t r1, uint32_t r2, uint32_t r3) {
  asm volatile("stmatrix.sync.aligned.m8n8.x4.shared.b16 [%0], {%1, %2, %3, %4};" ::"r"(a), "r"(r0), "r"(r1), "r"(r2), "r"(r3) : "memory");
}
__device__ __forceinline__ void stsm_t(uint32_t a, uint32_t r0, uint32_t r1, uint32_t r2, uint32_t r3) {
  asm volatile("stmatrix.sync.aligned.m8n8.x4.trans.shared.b16 [%0], {%1, %2, %3, %4};" ::"r"(a), "r"(r0), "r"(r1), "r"(r2), "r"(r3) : "memory");
}
__device__ __forceinline__ void ldsm(uint32_t a, uint32_t (&r)[4]) {
  asm volatile("ldmatrix.sync.aligned.m8n8.x4.shared.b16 {%0, %1, %2, %3}, [%4];"
               : "=r"(r[0]), "=r"(r[1]), "=r"(r[2]), "=r"(r[3]) : "r"(a) : "memory");
}
__device__ __forceinline__ void sts4u(uint32_t a, uint32_t x, uint32_t y, uint32_t z, uint32_t w) {
  asm volatile("st.shared.v4.u32 [%0], {%1, %2, %3, %4};" ::"r"(a), "r"(x), "r"(y), "r"(z), "r"(w) : "memory");
}
__device__ __forceinline__ void ldsm_t(uint32_t a, uint32_t (&r)[4]) {
  asm volatile("ldmatrix.sync.aligned.m8n8.x4.trans.shared.b16 {%0, %1, %2, %3}, [%4];"
               : "=r"(r[0]), "=r"(r[1]), "=r"(r[2]), "=r"(r[3]) : "r"(a) : "memory");
}
__device__ __forceinline__ float4 lds4f(uint32_t a) {
  float4 v; asm volatile("ld.shared.v4.f32 {%0, %1, %2, %3}, [%4];" : "=f"(v.x), "=f"(v.y), "=f"(v.z), "=f"(v.w) : "r"(a)); return v;
}
__device__ __forceinline__ float2 lds2f(uint32_t a) {
  float2 v; asm volatile("ld.shared.v2.f32 {%0, %1}, [%2];" : "=f"(v.x), "=f"(v.y) : "r"(a)); return v;
}
__device__ __forceinline__ float lds1f(uint32_t a) { float v; asm volatile("ld.shared.f32 %0, [%1];" : "=f"(v) : "r"(a)); return v; }
__device__ __forceinline__ uint4 lds4u(uint32_t a) {
  uint4 v; asm volatile("ld.shared.v4.u32 {%0, %1, %2, %3}, [%4];" : "=r"(v.x), "=r"(v.y), "=r"(v.z), "=r"(v.w) : "r"(a)); return v;
}
__device__ __forceinline__ uint32_t lds1u(uint32_t a) { uint32_t v; asm volatile("ld.shared.u32 %0, [%1];" : "=r"(v) : "r"(a)); return v; }
__device__ __forceinline__ void sts1f(uint32_t a, float v) { asm volatile("st.shared.f32 [%0], %1;" ::"r"(a), "f"(v) : "memory"); }
__device__ __forceinline__ void sts2f(uint32_t a, float x, float y) { asm volatile("st.shared.v2.f32 [%0], {%1, %2};" ::"r"(a), "f"(x), "f"(y) : "memory"); }
__device__ __forceinline__ uint4 ldg_nc(const void* p) {
  uint4 v; asm volatile("ld.global.nc.v4.u32 {%0, %1, %2, %3}, [%4];" : "=r"(v.x), "=r"(v.y), "=r"(v.z), "=r"(v.w) : "l"(p)); return v;
}
__device__ __forceinline__ void sumsq8(float& s0, float& s1, float& q0, float& q1, uint4 v) {
  float a, b;
  a = blo(v.x); b = bhi(v.x); s0 += a; s1 += b; q0 = fmaf(a, a, q0); q1 = fmaf(b, b, q1);
  a = blo(v.y); b = bhi(v.y); s0 += a; s1 += b; q0 = fmaf(a, a, q0); q1 = fmaf(b, b, q1);
  a = blo(v.z); b = bhi(v.z); s0 += a; s1 += b; q0 = fmaf(a, a, q0); q1 = fmaf(b, b, q1);
  a = blo(v.w); b = bhi(v.w); s0 += a; s1 += b; q0 = fmaf(a, a, q0); q1 = fmaf(b, b, q1);
}
__device__ __forceinline__ void acc8(float (&v)[8], uint4 q) {
  v[0] += blo(q.x); v[1] += bhi(q.x); v[2] += blo(q.y); v[3] += bhi(q.y);
  v[4] += blo(q.z); v[5] += bhi(q.z); v[6] += blo(q.w); v[7] += bhi(q.w);
}

__device__ __forceinline__ float2 colsum_warp(const bf16* p, int ld, int nb, int lane) {
  float v[8] = {0.f, 0.f, 0.f, 0.f, 0.f, 0.f, 0.f, 0.f};
  p += (lane >> 3) * ld + (lane & 7) * 8;
#pragma unroll 1
  for (; nb > 0; nb--) {
    uint4 q[8];
#pragma unroll
    for (int j = 0; j < 8; j++) q[j] = ldg_nc(p + j * 4 * ld);
#pragma unroll
    for (int j = 0; j < 8; j++) acc8(v, q[j]);
    p += 32 * ld;
  }
  bool u = lane & 16;
#pragma unroll
  for (int i = 0; i < 4; i++) { float s = u ? v[i] : v[i + 4], k = u ? v[i + 4] : v[i]; v[i] = k + __shfl_xor_sync(~0u, s, 16); }
  u = lane & 8;
#pragma unroll
  for (int i = 0; i < 2; i++) { float s = u ? v[i] : v[i + 2], k = u ? v[i + 2] : v[i]; v[i] = k + __shfl_xor_sync(~0u, s, 8); }
  return make_float2(v[0], v[1]);
}

template<int SB> __device__ __forceinline__ void wgmma_rs64(float (&d)[32], uint32_t a0, uint32_t a1, uint32_t a2, uint32_t a3, uint64_t db, int acc) {
  asm volatile("{\n.reg .pred p;\nsetp.ne.b32 p, %37, 0;\n"
    "wgmma.mma_async.sync.aligned.m64n64k16.f32.bf16.bf16 {%0, %1, %2, %3, %4, %5, %6, %7, %8, %9, %10, %11, %12, %13, %14, %15, %16, %17, %18, %19, %20, %21, %22, %23, %24, %25, %26, %27, %28, %29, %30, %31}, {%32, %33, %34, %35}, %36, p, 1, %38, 0;\n}\n"
    : "+f"(d[0]), "+f"(d[1]), "+f"(d[2]), "+f"(d[3]), "+f"(d[4]), "+f"(d[5]), "+f"(d[6]), "+f"(d[7]), "+f"(d[8]), "+f"(d[9]), "+f"(d[10]), "+f"(d[11]), "+f"(d[12]), "+f"(d[13]), "+f"(d[14]), "+f"(d[15]), "+f"(d[16]), "+f"(d[17]), "+f"(d[18]), "+f"(d[19]), "+f"(d[20]), "+f"(d[21]), "+f"(d[22]), "+f"(d[23]), "+f"(d[24]), "+f"(d[25]), "+f"(d[26]), "+f"(d[27]), "+f"(d[28]), "+f"(d[29]), "+f"(d[30]), "+f"(d[31])
    : "r"(a0), "r"(a1), "r"(a2), "r"(a3), "l"(db), "r"(acc), "n"(SB));
}
template<int TA, int TB> __device__ __forceinline__ void wgmma_ss192(float (&d)[96], uint64_t da, uint64_t db, int acc) {
  asm volatile("{\n.reg .pred p;\nsetp.ne.b32 p, %98, 0;\n"
    "wgmma.mma_async.sync.aligned.m64n192k16.f32.bf16.bf16 {%0, %1, %2, %3, %4, %5, %6, %7, %8, %9, %10, %11, %12, %13, %14, %15, %16, %17, %18, %19, %20, %21, %22, %23, %24, %25, %26, %27, %28, %29, %30, %31, %32, %33, %34, %35, %36, %37, %38, %39, %40, %41, %42, %43, %44, %45, %46, %47, %48, %49, %50, %51, %52, %53, %54, %55, %56, %57, %58, %59, %60, %61, %62, %63, %64, %65, %66, %67, %68, %69, %70, %71, %72, %73, %74, %75, %76, %77, %78, %79, %80, %81, %82, %83, %84, %85, %86, %87, %88, %89, %90, %91, %92, %93, %94, %95}, %96, %97, p, 1, 1, %99, %100;\n}\n"
    : "+f"(d[0]), "+f"(d[1]), "+f"(d[2]), "+f"(d[3]), "+f"(d[4]), "+f"(d[5]), "+f"(d[6]), "+f"(d[7]), "+f"(d[8]), "+f"(d[9]), "+f"(d[10]), "+f"(d[11]), "+f"(d[12]), "+f"(d[13]), "+f"(d[14]), "+f"(d[15]), "+f"(d[16]), "+f"(d[17]), "+f"(d[18]), "+f"(d[19]), "+f"(d[20]), "+f"(d[21]), "+f"(d[22]), "+f"(d[23]), "+f"(d[24]), "+f"(d[25]), "+f"(d[26]), "+f"(d[27]), "+f"(d[28]), "+f"(d[29]), "+f"(d[30]), "+f"(d[31]), "+f"(d[32]), "+f"(d[33]), "+f"(d[34]), "+f"(d[35]), "+f"(d[36]), "+f"(d[37]), "+f"(d[38]), "+f"(d[39]), "+f"(d[40]), "+f"(d[41]), "+f"(d[42]), "+f"(d[43]), "+f"(d[44]), "+f"(d[45]), "+f"(d[46]), "+f"(d[47]), "+f"(d[48]), "+f"(d[49]), "+f"(d[50]), "+f"(d[51]), "+f"(d[52]), "+f"(d[53]), "+f"(d[54]), "+f"(d[55]), "+f"(d[56]), "+f"(d[57]), "+f"(d[58]), "+f"(d[59]), "+f"(d[60]), "+f"(d[61]), "+f"(d[62]), "+f"(d[63]), "+f"(d[64]), "+f"(d[65]), "+f"(d[66]), "+f"(d[67]), "+f"(d[68]), "+f"(d[69]), "+f"(d[70]), "+f"(d[71]), "+f"(d[72]), "+f"(d[73]), "+f"(d[74]), "+f"(d[75]), "+f"(d[76]), "+f"(d[77]), "+f"(d[78]), "+f"(d[79]), "+f"(d[80]), "+f"(d[81]), "+f"(d[82]), "+f"(d[83]), "+f"(d[84]), "+f"(d[85]), "+f"(d[86]), "+f"(d[87]), "+f"(d[88]), "+f"(d[89]), "+f"(d[90]), "+f"(d[91]), "+f"(d[92]), "+f"(d[93]), "+f"(d[94]), "+f"(d[95])
    : "l"(da), "l"(db), "r"(acc), "n"(TA), "n"(TB));
}
template<int TA, int TB> __device__ __forceinline__ void wgmma_ss64(float (&d)[32], uint64_t da, uint64_t db, int acc) {
  asm volatile("{\n.reg .pred p;\nsetp.ne.b32 p, %34, 0;\n"
    "wgmma.mma_async.sync.aligned.m64n64k16.f32.bf16.bf16 {%0, %1, %2, %3, %4, %5, %6, %7, %8, %9, %10, %11, %12, %13, %14, %15, %16, %17, %18, %19, %20, %21, %22, %23, %24, %25, %26, %27, %28, %29, %30, %31}, %32, %33, p, 1, 1, %35, %36;\n}\n"
    : "+f"(d[0]), "+f"(d[1]), "+f"(d[2]), "+f"(d[3]), "+f"(d[4]), "+f"(d[5]), "+f"(d[6]), "+f"(d[7]), "+f"(d[8]), "+f"(d[9]), "+f"(d[10]), "+f"(d[11]), "+f"(d[12]), "+f"(d[13]), "+f"(d[14]), "+f"(d[15]), "+f"(d[16]), "+f"(d[17]), "+f"(d[18]), "+f"(d[19]), "+f"(d[20]), "+f"(d[21]), "+f"(d[22]), "+f"(d[23]), "+f"(d[24]), "+f"(d[25]), "+f"(d[26]), "+f"(d[27]), "+f"(d[28]), "+f"(d[29]), "+f"(d[30]), "+f"(d[31])
    : "l"(da), "l"(db), "r"(acc), "n"(TA), "n"(TB));
}
template<int TA, int TB> __device__ __forceinline__ void wgmma_ss80(float (&d)[40], uint64_t da, uint64_t db, int acc) {
  asm volatile("{\n.reg .pred p;\nsetp.ne.b32 p, %42, 0;\n"
    "wgmma.mma_async.sync.aligned.m64n80k16.f32.bf16.bf16 {%0, %1, %2, %3, %4, %5, %6, %7, %8, %9, %10, %11, %12, %13, %14, %15, %16, %17, %18, %19, %20, %21, %22, %23, %24, %25, %26, %27, %28, %29, %30, %31, %32, %33, %34, %35, %36, %37, %38, %39}, %40, %41, p, 1, 1, %43, %44;\n}\n"
    : "+f"(d[0]), "+f"(d[1]), "+f"(d[2]), "+f"(d[3]), "+f"(d[4]), "+f"(d[5]), "+f"(d[6]), "+f"(d[7]), "+f"(d[8]), "+f"(d[9]), "+f"(d[10]), "+f"(d[11]), "+f"(d[12]), "+f"(d[13]), "+f"(d[14]), "+f"(d[15]), "+f"(d[16]), "+f"(d[17]), "+f"(d[18]), "+f"(d[19]), "+f"(d[20]), "+f"(d[21]), "+f"(d[22]), "+f"(d[23]), "+f"(d[24]), "+f"(d[25]), "+f"(d[26]), "+f"(d[27]), "+f"(d[28]), "+f"(d[29]), "+f"(d[30]), "+f"(d[31]), "+f"(d[32]), "+f"(d[33]), "+f"(d[34]), "+f"(d[35]), "+f"(d[36]), "+f"(d[37]), "+f"(d[38]), "+f"(d[39])
    : "l"(da), "l"(db), "r"(acc), "n"(TA), "n"(TB));
}
template<int TA, int TB> __device__ __forceinline__ void wgmma_ss88(float (&d)[44], uint64_t da, uint64_t db, int acc) {
  asm volatile("{\n.reg .pred p;\nsetp.ne.b32 p, %46, 0;\n"
    "wgmma.mma_async.sync.aligned.m64n88k16.f32.bf16.bf16 {%0, %1, %2, %3, %4, %5, %6, %7, %8, %9, %10, %11, %12, %13, %14, %15, %16, %17, %18, %19, %20, %21, %22, %23, %24, %25, %26, %27, %28, %29, %30, %31, %32, %33, %34, %35, %36, %37, %38, %39, %40, %41, %42, %43}, %44, %45, p, 1, 1, %47, %48;\n}\n"
    : "+f"(d[0]), "+f"(d[1]), "+f"(d[2]), "+f"(d[3]), "+f"(d[4]), "+f"(d[5]), "+f"(d[6]), "+f"(d[7]), "+f"(d[8]), "+f"(d[9]), "+f"(d[10]), "+f"(d[11]), "+f"(d[12]), "+f"(d[13]), "+f"(d[14]), "+f"(d[15]), "+f"(d[16]), "+f"(d[17]), "+f"(d[18]), "+f"(d[19]), "+f"(d[20]), "+f"(d[21]), "+f"(d[22]), "+f"(d[23]), "+f"(d[24]), "+f"(d[25]), "+f"(d[26]), "+f"(d[27]), "+f"(d[28]), "+f"(d[29]), "+f"(d[30]), "+f"(d[31]), "+f"(d[32]), "+f"(d[33]), "+f"(d[34]), "+f"(d[35]), "+f"(d[36]), "+f"(d[37]), "+f"(d[38]), "+f"(d[39]), "+f"(d[40]), "+f"(d[41]), "+f"(d[42]), "+f"(d[43])
    : "l"(da), "l"(db), "r"(acc), "n"(TA), "n"(TB));
}

__device__ __forceinline__ uint32_t hmul2(uint32_t a, uint32_t b) { uint32_t d; asm("mul.rn.bf16x2 %0, %1, %2;" : "=r"(d) : "r"(a), "r"(b)); return d; }
__device__ __forceinline__ uint32_t hfma2(uint32_t a, uint32_t b, uint32_t c) { uint32_t d; asm("fma.rn.bf16x2 %0, %1, %2, %3;" : "=r"(d) : "r"(a), "r"(b), "r"(c)); return d; }

template <int SKIP, int NSLOT> __device__ __forceinline__ uint32_t next_slot(uint32_t s) {
  s++;
  if (SKIP >= 0 && s == (uint32_t)SKIP) s++;
  return s == NSLOT ? 0 : s;
}

template <int TA, int SKIP, int NSLOT, bool FIRST = true, bool LAST = true, bool INIT = false>
__device__ __forceinline__ void gemm80_loop(float (&acc)[40], uint32_t sb, int op0, uint32_t slot, int nst, int wg, bool sig, int rankB, const Params& PP) {
#pragma unroll 1
  for (int st = 0; st < nst; st++) {
    mbar_wait(sb + O_FULL + 8 * (op0 + st), 0);
    if (sig && wg == 0) STAMP2(0, op0 + st);
    uint32_t base = sb + slot * SLOT;
    Desc da = desc(base + wg * 8192, TA ? 8192 : 16), db = desc(base + 16384, 16);
    wg_fence();
#pragma unroll
    for (int k = 0; k < 4; k++) wgmma_ss80<TA, 0>(acc, da + k * (TA ? 128 : 2), db + k * 2, INIT || (st | k) != 0);
    wg_commit();
    wg_wait<1>();
    if ((st || !FIRST) && sig) mbar_arrive(sb + O_EMPTY + 8 * (op0 + st - 1));
    slot = next_slot<SKIP, NSLOT>(slot);
  }
  if (LAST) {
    wg_wait<0>();
    if (sig) mbar_arrive(sb + O_EMPTY + 8 * (op0 + nst - 1));
  }
}

template <int NSLOT>
__device__ __forceinline__ void f1_loop(float (&a0)[40], float (&a1)[40], uint32_t sb, int st0, int st1, uint32_t slot, bool sig, int rankB, const Params& PP) {
#pragma unroll 1
  for (int st = st0; st < st1; st++) {
    mbar_wait(sb + O_FULL + 8 * (11 + st), 0);
    if (sig) STAMP2(0, 11 + st);
    uint32_t base = sb + slot * SLOT;
    Desc da = desc(base, 16), db = desc(base + 16384, 16);
    wg_fence();
#pragma unroll
    for (int k = 0; k < 4; k++) {
      wgmma_ss80<0, 0>(a0, da + k * 2, db + k * 2, (st | k) != 0);
      wgmma_ss80<0, 0>(a1, da + 512 + k * 2, db + k * 2, (st | k) != 0);
    }
    wg_commit();
    wg_wait<1>();
    if (st != st0 && sig) mbar_arrive(sb + O_EMPTY + 8 * (10 + st));
    slot = next_slot<-1, NSLOT>(slot);
  }
  wg_wait<0>();
  if (sig) mbar_arrive(sb + O_EMPTY + 8 * (10 + st1));
}

template <bool CONJ>
__device__ __forceinline__ void cmul(const float (&d)[32], const uint32_t (&f)[16], uint32_t (&ac)[16], uint32_t (&as)[16]) {
#pragma unroll
  for (int i = 0; i < 8; i++) {
    const uint32_t re = pack(d[4 * i], d[4 * i + 1]), im = pack(d[4 * i + 2], d[4 * i + 3]);
    ac[2 * i] = hfma2(re, f[2 * i], hmul2(im, f[2 * i + 1] ^ 0x80008000u));
    as[2 * i] = hfma2(re, f[2 * i + 1], hmul2(im, f[2 * i]));
    asm volatile("xor.b32 %0, %1, %2;" : "=r"(ac[2 * i + 1]) : "r"(as[2 * i]), "n"(CONJ ? 0x80008000u : 0u));
    asm volatile("xor.b32 %0, %1, %2;" : "=r"(as[2 * i + 1]) : "r"(ac[2 * i]), "n"(CONJ ? 0u : 0x80008000u));
  }
}
template <bool CONJ>
__device__ __forceinline__ void dft64(float (&d)[32], const uint32_t (&ac)[16], const uint32_t (&as)[16], Desc dc) {
  wg_fence();
#pragma unroll
  for (int k = 0; k < 4; k++) {
    wgmma_rs64<1>(d, ac[4 * k], ac[4 * k + 1], ac[4 * k + 2], ac[4 * k + 3], dc + k * 2, k != 0);
    wgmma_rs64<CONJ ? -1 : 1>(d, as[4 * k], as[4 * k + 1], as[4 * k + 2], as[4 * k + 3], dc + 512 + k * 2, 1);
  }
  wg_commit();
  wg_wait<0>();
}

__device__ __forceinline__ void init_range(int r, int lane, bool hasA, bool hasB, int rankB) {
      constexpr uint32_t sb = SB;
      if (elect()) {
        const bool live = r == 1 ? hasB : r < 3 ? hasA : true;
        const uint32_t fa = sb + O_FULL + 64 + r * 80, ea = sb + O_EMPTY + r * 88;
        const uint32_t ec = (!live || r == 1) ? 1 : 2;
#pragma unroll
        for (int i = 0; i < 10; i++) mbar_init(fa + 8 * i, 1);
#pragma unroll
        for (int i = 0; i < 10; i++) mbar_init(ea + 8 * i, (r == 7 && i) ? 1 : ec);
        mbar_init(ea + 80, (r == 0 || r == 3) ? 1 : ec);
        if (!live) {
#pragma unroll 1
          for (int i = 0; i < 11; i++) mbar_arrive(ea + 8 * i);
        }
        if (r == 7) {
          mbar_arrive(sb + O_EMPTY + 8 * E_NONE);
          mbar_init(sb + O_EMPTY + 8 * 83, rankB < 56 ? 3 : 2);
        }
        if (r == 3 && !hasB) {
          mbar_init(sb + O_EMPTY + 8 * 39, 1); mbar_init(sb + O_EMPTY + 8 * 40, 1);
          mbar_arrive(sb + O_EMPTY + 8 * 43);
        }
        asm volatile("fence.mbarrier_init.release.cluster;" ::: "memory");
      }
      __syncwarp();
      if (lane < 10) {
        const int op = 8 + r * 10 + lane;
        mbar_expect_tx(sb + O_FULL + 8 * op, op >= 82 ? 8192 : (op == 32 || op >= 78) ? 20480 : (op >= 33 && op <= 42) ? QSLOT : SLOT);
      }
      __syncwarp();
}

template <bool BY_SMID>
__global__ void __launch_bounds__(512, 1) fused_kernel(const __grid_constant__ Params P) {
  extern __shared__ __align__(1024) uint8_t smem_raw[];
  constexpr uint32_t sb = SB;
  const int tid = threadIdx.x, lane = tid & 31;
  const int warp = __shfl_sync(~0u, tid >> 5, 0);

  if (warp == 13) {
    if (elect()) {
      asm volatile("prefetch.tensormap [%0];" ::"l"(&P.m[L_W1]) : "memory");
      asm volatile("prefetch.tensormap [%0];" ::"l"(&P.m[L_X80]) : "memory");
    }
    __syncwarp();
  } else if (warp >= 8 && warp < 12 && blockIdx.x < 128) {
    const int u = tid - 256;
    if (u < 16 * EARLY_PF) l2_prefetch(P.x + (blockIdx.x * 16 + (u & 15)) * 640 + (u >> 4) * 64);
    if (u >= 128 - 8 * EARLY_PF && (u & 7) < 5) l2_prefetch(P.w1 + ((15 - (u >> 3)) * 640 + blockIdx.x * 5 + (u & 7)) * 64);
    __syncwarp();
  }
  unsigned smid = blockIdx.x;
  if (BY_SMID) asm("mov.u32 %0, %%smid;" : "=r"(smid));
  smid = __shfl_sync(~0u, smid, 0);
  const int gp = gpc_pos(smid), rankA = rank_a(gp), rankB = rank_b(gp);
  const bool hasA = rankA < 130, hasB = rankB < 128;
  const int tb = rankA / 5, fb = rankA % 5;
  const int task = rankB < 92 ? rankB : rankB < 96 ? 127 : rankB - 4;
  const int rb = RB_OF(rankB), cb = CB_OF(rankB);

  if (warp >= 12) {
    asm volatile("setmaxnreg.dec.sync.aligned.u32 56;");
    if (warp < 14) {
      const bool pa = warp == 13;
      if (!pa && elect()) {
#pragma unroll
        for (int i = 0; i < 8; i++) mbar_init(sb + O_FULL + 8 * i, 1);
        mbar_init(sb + O_BAR + 8 * B_XS, 1);
        mbar_expect_tx(sb + O_BAR + 8 * B_XS, 20480);
#pragma unroll
        for (int i = 0; i < 8; i++) mbar_expect_tx(sb + O_FULL + 8 * i, SLOT);
        asm volatile("fence.mbarrier_init.release.cluster;" ::: "memory");
      }
      __syncwarp();
      asm volatile("bar.arrive 0, 512;" ::: "memory");
      if (pa && hasB && lane < 15) l2_prefetch(P.w1 + 448 * 640 + (rankB * 15 + lane) * 64);
      if (hasA && !pa && elect()) {
        if (XS_AFTER < 0 && rankA < 128) bulk_ld(sb + O_XS, P.x + rankA * 16 * 640, 20480, sb + O_BAR + 8 * B_XS);
#pragma unroll 1
        for (int i = 0; i < 7; i++) {
          tma3(sb + i * G1SLOT, &P.m[L_W1], 0, i * 64, fb * 2, sb + O_FULL + 8 * i);
          tma3(sb + i * G1SLOT + 16384, &P.m[L_X80], 0, tb * 80, i, sb + O_FULL + 8 * i);
          if (i == XS_AFTER && rankA < 128) bulk_ld(sb + O_XS, P.x + rankA * 16 * 640, 20480, sb + O_BAR + 8 * B_XS);
        }
        STAMP(40);
      }
      if (OPS_WARM && pa) asm volatile("st.shared.u32 [%0], %1;" ::"r"(sb + O_RB + lane * 4), "r"(P.ops.v[min(lane, 9) * 16 + 7]) : "memory");
      __syncwarp();
      bar_sync(4, 96);
      {
#pragma unroll 1
        for (int ph = 0; ph < (hasB ? (pa ? 5 : 6) : 3); ph++) {
          int op, n = 10, map, c1 = 0, c2 = 0, d1 = 0, d2 = 1, pc = 0, pn = 0, pm = 0;
          bool valid = true;
          if (ph == 0 || ph == 2) {
            valid = hasA;
            op = ph ? 22 : 7; n = ph ? 10 : 3;
            if (pa) {
              map = ph ? L_SC80 : L_X80; c1 = tb * 80 + (ph ? ROW_H : 0); c2 = ph ? 0 : 7;
              if (ph) { pc = C_H + max(tb - 1, 0); pn = (tb == 0 || tb == 25) ? 2 : 3; pm = N_H; }
            } else { map = ph ? L_W2 : L_W1; c1 = ph ? 0 : 448; d1 = 64; c2 = fb * 2; d2 = 0; }
          } else if (ph == 1) {
            valid = hasB; op = 11; n = 6; map = pa ? L_T : L_X128; c1 = pa ? cb * 80 : rb * 128;
          } else if (ph == 3) {
            op = 33;
            if (pa) { map = L_SC128; c1 = ROW_X1 + rb * 128; pc = C_X1 + rb * 8 / 5; pn = (rb * 128 + 127) / 80 - rb * 8 / 5 + 1; pm = N_X1; }
            else { map = L_W3; d1 = 64; c2 = cb * 3; d2 = 0; }
          } else if (ph == 5) {
            op = 68; map = L_T; c1 = 640 + cb * 80;
          } else {
            op = 44; n = 24;
            if (pa) { map = L_H2; c1 = rb * 128; pc = C_H2 + rb; pn = 1; pm = N_H2; }
            else { map = L_W4T; c1 = cb * 80; }
          }
          const CUtensorMap* mp = &P.m[map];
          if (elect()) asm volatile("prefetch.tensormap [%0];" ::"l"(mp) : "memory");
          __syncwarp();
          const uint32_t* tab = P.ops.v + (pa ? 80 : 0);
          uint32_t e = tab[op];
          if (pn && valid) {
            mbar_wait(sb + O_BAR + 8 * B_EP, 0);
            poll(P, pc, pn, lds1u(sb + O_EP) * pm, lane);
            fence_async_gmem();
          }
          if (F1_HOLD && ph == 1 && valid) mbar_wait(sb + O_EMPTY + 8 * F1_HOLD, 0);
          if (valid && !pa && (ph == 2 || ph == 4)) {
            if (ph == 4) mbar_wait(sb + O_BAR + 8 * B_WOK, 0);
            mbar_wait(sb + O_BAR + 8 * (ph == 2 ? B_PUB1 : B_PUB3), 0);
            fence_async_gmem();
          }
#pragma unroll 1
          for (; n > 0; n--) {
            const uint32_t nx = tab[op + 1];
            mbar_wait(O_MISC + (e >> 18), 0);
            if (valid && elect()) tma3(e & 0x3ffff, mp, 0, c1, c2, sb + O_FULL + 8 * op);
            __syncwarp();
            c1 += d1; c2 += d2; op++; e = nx;
          }
        }
      }
    } else {
      const int aw = warp - 14;
      if ((uint32_t)__cvta_generic_to_shared(smem_raw) != SB) __trap();
      if (aw == 1 && elect()) {
#pragma unroll
        for (int b = 0; b < B_COUNT; b++) mbar_init(sb + O_BAR + 8 * b, b == B_STAT3 ? 128 : b < B_UW ? 1 : (b < B_HW || b >= B_H2A) ? 4 : 8);
        asm volatile("fence.mbarrier_init.release.cluster;" ::: "memory");
      }
      __syncwarp();
      bar_sync(0, 512);
      if (aw == 1) asm volatile("bar.arrive 4, 96;" ::: "memory");
      else asm volatile("bar.arrive 5, 160;" ::: "memory");
      mbar_wait(sb + O_BAR + 8 * B_EP, 0);
      const unsigned ep = lds1u(sb + O_EP);
      if (aw == 0) {
        if (hasA) {
          if (lane < 3) asm volatile("prefetch.tensormap [%0];" ::"l"(&P.m[M_HST + lane]) : "memory");
          int hr[4];
#pragma unroll
          for (int i = 0; i < 4; i++) {
            const int f = fb * 128 + i * 32;
            hr[i] = tb * 80 + ROW_H + (f < 160 ? 1 : f < 320 ? -1 : f < 480 ? 2 : -2);
          }
#pragma unroll
          for (int hf = 0; hf < 2; hf++) {
            mbar_wait(sb + O_BAR + 8 * (B_HW + hf), 0);
            if (elect()) {
#pragma unroll
              for (int i = 0; i < 4; i++) tma2_st(&P.m[M_HST], sb + O_STG + i * 5120 + hf * 2560, fb * 128 + i * 32, hr[i] + hf * 40);
            }
            __syncwarp();
          }
          if (elect()) {
            publish(P, sb + O_EMPTY + 8 * 10, C_H + tb, rankB, 48);
            mbar_arrive(sb + O_BAR + 8 * B_PUB1);
          }
          __syncwarp();
          if (hasB) {
#pragma unroll 1
            for (int k = 6; k < 10; k++) {
              mbar_wait(sb + O_EMPTY + 8 * min(19 + F1C_D + k, 30), 0);
              const uint32_t dst = sb + (k == 6 ? 3 : k - 7) * SLOT, fbar = sb + O_FULL + 8 * (11 + k);
              if (elect()) {
                tma3(dst, &P.m[L_X128], 0, rb * 128, k, fbar);
                tma3(dst + 16384, &P.m[L_T], 0, cb * 80, k, fbar);
              }
              __syncwarp();
            }
            mbar_wait(sb + O_BAR + 8 * B_WTST, 0);
          }
          mbar_wait(sb + O_BAR + 8 * B_X1W, 0);
          if (elect()) {
            tma3_st(&P.m[M_X1ST], sb + O_X1S, 0, ROW_X1 + tb * 80, fb * 2);
            publish(P, sb + O_BAR + 8 * B_X1ST, C_X1 + tb, rankB, 50);
            if (hasB) red_relaxed(P, C_U);
            mbar_arrive(sb + O_BAR + 8 * B_PUB2);
          }
          __syncwarp();
        }
        if (hasB) {
          mbar_wait(sb + O_EMPTY + 8 * 40, 0);
          if (lane < 2) asm volatile("prefetch.tensormap [%0];" ::"l"(&P.m[lane ? M_H2H : L_H2]) : "memory");
          __syncwarp();
#pragma unroll
          for (int i = 1; i >= 0; i--) {
            mbar_wait(sb + O_BAR + 8 * (B_H2A + i), 0);
            if (elect()) tma3_st(&P.m[M_H2H], sb + O_STG3 + i * 8192, 0, rb * 128 + i * 64, cb * 3);
            __syncwarp();
          }
#pragma unroll
          for (int sub = 1; sub < 3; sub++) {
            mbar_wait(sb + O_BAR + 8 * (B_H2W + sub), 0);
            if (elect()) tma3_st(&P.m[L_H2], sb + O_STG3 + sub * 16384, 0, rb * 128, cb * 3 + sub);
            __syncwarp();
          }
          if (elect()) {
            publish(P, sb + O_EMPTY + 8 * 43, C_H2 + rb, rankB, 52);
            mbar_arrive(sb + O_BAR + 8 * B_PUB3);
          }
          __syncwarp();
          mbar_wait(sb + O_EMPTY + 8 * 52, 0);
          if (elect()) asm volatile("prefetch.tensormap [%0];" ::"l"(&P.m[L_V]) : "memory");
          __syncwarp();
          poll(P, C_V, 1, ep * N_V, lane);
          if (lane == 0) STAMP(4);
          fence_async_gmem();
          __syncwarp();
          uint32_t slot = 1;
#pragma unroll 1
          for (int k = 0; k < 10; k++) {
            mbar_wait(sb + O_EMPTY + 8 * (61 + k), 0);
            if (elect()) tma3(sb + slot * SLOT, &P.m[L_V], 0, k * 64, rb * 2, sb + O_FULL + 8 * (68 + k));
            __syncwarp();
            slot = next_slot<-1, 7>(slot);
          }
        }
      } else {
        const uint32_t rbar = sb + O_BAR + 8 * B_RB;
        const int ncol = rankB < 56 ? 3 : 2;
        if (!hasB) mbar_wait(sb + O_BAR + 8 * B_XSD, 0);
        if (hasA) {
          mbar_wait(sb + O_EMPTY + 8 * XT_OP, 0);
          if (XT_HOLD) mbar_wait(sb + O_BAR + 8 * B_STAT1, 0);
          if (elect()) tma3(sb + O_XT, &P.m[L_XT], 0, tb * 80, fb * 2, sb + O_FULL + 8 * 32);
          __syncwarp();
        }
        if (hasB) {
          if (lane < 2) asm volatile("prefetch.tensormap [%0];" ::"l"(&P.m[L_W4 + lane]) : "memory");
#pragma unroll 1
          for (int i = 0; i < 4; i++) {
            mbar_wait(sb + O_EMPTY + 8 * (i + PF0), 0);
            if (lane < 25) l2_prefetch((i < 2 ? P.dft : P.w2) + rankB * 3200 + ((i & 1) * 25 + lane) * 64);
          }
          mbar_wait(sb + O_BAR + 8 * B_XSD, 0);
          mbar_wait(sb + O_EMPTY + 8 * W4_OP, 0);
          if (task < 120) {
            if (elect()) {
              mbar_expect_tx(sb + O_BAR + 8 * B_W4LD, 16384);
              tma3(sb + O_WORK, &P.m[L_W4], 0, (task / 5) * 64, (task % 5) * 2, sb + O_BAR + 8 * B_W4LD);
            }
            __syncwarp();
            if (lane == 0) STAMP(28);
            mbar_wait(sb + O_BAR + 8 * B_W4W, 0);
          }
#pragma unroll 1
          for (int i = 0; i < 10; i++) {
            mbar_wait(i ? sb + O_EMPTY + 8 * (21 + i) : sb + O_FULL + 8 * 22, 0);
            if (task < 120 && i < 8 && elect()) tma3_st(&P.m[M_W4T], sb + O_WORK + i * 2048, 0, (task % 5) * 128 + i * 16, task / 5);
            const bf16* p = i < 6 ? (i < 3 ? P.wr + i * 1728 : P.wi + (i - 3) * 1728) + rankB * 5136 : P.w3 + rankB * 7680 + (i - 6) * 1920;
            if (lane < (i < 6 ? 27 : 30)) l2_prefetch(p + lane * 64);
            __syncwarp();
          }
          if (elect()) { st_commit(); st_wait_all(); mbar_arrive(sb + O_BAR + 8 * B_WTST); STAMP(20); }
          if (lane < 7) asm volatile("prefetch.tensormap [%0];" ::"l"(&P.m[L_WR + lane]) : "memory");
          __syncwarp();
          mbar_wait(WLD_GATE, 0);
          if (elect()) {
            const int c0 = (rankB & 31) * 321 / 8 * 8 + (rankB >> 6) * 168, c1 = rankB & 32;
            mbar_expect_tx(sb + O_BAR + 8 * B_WLD, 2 * 10752);
            tma2(sb + O_WORK, &P.m[L_WR], c0, c1, sb + O_BAR + 8 * B_WLD);
            tma2(sb + O_WORK + 10752, &P.m[L_WI], c0, c1, sb + O_BAR + 8 * B_WLD);
            STAMP(9);
          }
          __syncwarp();
          const int w0 = (rankB & 31) * 128 + (rankB & 32) * 2, w1 = 8 - ((rankB & 31) * 321 & 7) + (rankB >> 6) * 168;
          mbar_wait(sb + O_BAR + 8 * B_UW, 0);
#pragma unroll 1
          for (int i = 0; i < 5; i++) {
            if (i == 2) mbar_wait(sb + O_BAR + 8 * B_WTW, 0);
            mbar_wait(sb + O_FULL + 8 * (WT_OP + i), 0);
            if (elect()) {
              if (i < 2) tma2_st(&P.m[M_UST], sb + O_X1S + i * 10240, rb * 128 + i * 64, cb * 80);
              else tma2_st(&P.m[M_WT], sb + O_WORK + (i - 2) * 7168, w0, w1 + (i - 2) * 56);
            }
            __syncwarp();
          }
          if (elect()) {
            st_commit();
            st_wait_all();
            mbar_arrive(sb + O_EMPTY + 8 * 85);
            STAMP(7);
            mbar_expect_tx(rbar, (168 + 160) * 16);
            tma2(sb + O_RB + 2816, &P.m[R_U], rb * 128, cb * 80, rbar);
            tma2(sb + O_RB + 4096, &P.m[R_U], rb * 128 + 64, cb * 80, rbar);
            tma2(sb + O_RB, &P.m[R_WT], w0, w1, rbar);
          }
          __syncwarp();
          mbar_wait(rbar, 0);
          if (lane == 0) { red_relaxed(P, C_U); STAMP(13); }
        }
        mbar_wait(sb + O_EMPTY + 8 * 39, 0);
        if (elect()) {
          mbar_expect_tx(sb + O_BAR + 8 * B_MAT, 24576);
          bulk_ld(sb + O_M32, P.fft, 24576, sb + O_BAR + 8 * B_MAT);
        }
        __syncwarp();
        poll(P, C_U, 1, ep * N_U, lane);
        fence_async_gmem();
        if (lane == 0) { mbar_arrive(sb + O_BAR + 8 * B_WOK); STAMP(21); }
        mbar_wait(sb + O_EMPTY + 8 * 40, 0);
        if (elect()) {
#pragma unroll 1
          for (int i = 0; i < ncol; i++) tma3(sb + O_FD + i * 8192, &P.m[L_U], 0, 0, rankB + 132 * i, sb + O_FULL + 8 * (82 + i));
        }
        __syncwarp();
        mbar_wait(sb + O_EMPTY + 8 * (hasB ? 41 : 40), 0);
        if (elect()) {
          mbar_expect_tx(sb + O_BAR + 8 * B_FAC, ncol * 8192);
          bulk_ld(sb + O_FAC, P.fft + 24576, 8192, sb + O_BAR + 8 * B_FAC);
          bulk_ld(sb + O_FAC + 8192, P.Wt + (rankB + 140) * WT_LD, 8192, sb + O_BAR + 8 * B_FAC);
          if (ncol == 3) bulk_ld(sb + O_FAC + 16384, P.Wt + (rankB + 272) * WT_LD, 8192, sb + O_BAR + 8 * B_FAC);
        }
        if (lane < 2) asm volatile("prefetch.tensormap [%0];" ::"l"(&P.m[M_VST + lane]) : "memory");
        __syncwarp();
        if (hasB) mbar_wait(sb + O_BAR + 8 * B_PUB3, 0);
#pragma unroll 1
        for (int i = 0; i < 4 * ncol; i++) {
          if ((i & 3) == 0) mbar_wait(sb + O_BAR + 8 * (B_VW + (i >> 2)), 0);
          if (hasB && i >= 4 && (i & ((1 << V_SH) - 1)) == 0) mbar_wait(i == 4 ? sb + O_FULL + 8 * V_OP : sb + O_EMPTY + 8 * (43 + ((i - 4) >> V_SH)), 0);
          if (elect()) tma3_st(&P.m[M_VST], sb + O_WORK + i * 2048, 0, (i & 3) * 16, 320 + rankB + 132 * (i >> 2));
          __syncwarp();
        }
        if (elect()) {
          st_commit();
          st_wait_all();
          STAMP(54);
          mbar_expect_tx(rbar, ncol * 1024);
#pragma unroll 1
          for (int i = 0; i < ncol; i++) tma3(sb + O_RB + i * 1024, &P.m[R_V], 0, 0, 320 + rankB + 132 * i, rbar);
        }
        __syncwarp();
        mbar_wait(rbar, hasB);
        if (lane == 0) { red_relaxed(P, C_V); STAMP(55); }
        if (hasB) {
          if (lane < 3) asm volatile("prefetch.tensormap [%0];" ::"l"(&P.m[L_XF + lane]) : "memory");
          fence_async_gmem();
          __syncwarp();
          mbar_wait(sb + O_EMPTY + 8 * X1F_OP, 0);
          if (elect()) tma2(sb + O_WORK, &P.m[L_X1F], cb * 80, rb * 128, sb + O_FULL + 8 * 79);
          __syncwarp();
          mbar_wait(sb + O_EMPTY + 8 * 71, 0);
          if (elect()) tma2(sb + 4 * SLOT, &P.m[L_XF], cb * 80, rb * 128, sb + O_FULL + 8 * 78);
          __syncwarp();
        }
      }
    }
  } else {
    asm volatile("setmaxnreg.inc.sync.aligned.u32 152;");
    const int wg = warp >> 2, ww = warp & 3, g = lane >> 2, q = lane & 3, t = tid & 127;
    const bool sig = t == 0;
    const uint32_t tr_off = (uint32_t)((lane >> 4) * 8 + (lane & 7)) * 128 + (uint32_t)(((2 * ww + ((lane >> 3) & 1)) ^ (lane & 7)) << 4);
    const int ci = wg == 2 ? 0 : wg + 1, col = rankB + 132 * ci;
    unsigned ep = 0;
    uint32_t tw[16], wf[16];
    float rs0 = 0.f, rs1 = 0.f;

    if (wg == 2) {
      {
        uint4 xr[10];
        if (sig) STAMP(44);
        asm volatile("bar.arrive 0, 512;" ::: "memory");
        if (sig) asm volatile("atom.relaxed.gpu.global.add.u32 %0, [%1], 1;" : "=r"(ep) : "l"(P.sm->cnt + C_EPOCH * 32) : "memory");
        bar_sync(5, 160);
        if (sig) {
          asm volatile("st.shared.v2.u32 [%0], {%1, 0};" ::"r"(sb + O_EP), "r"(ep / N_EPOCH + 1) : "memory");
          mbar_arrive(sb + O_BAR + 8 * B_EP);
        }
        __syncwarp();
#pragma unroll 1
        for (int r = 7 - ww; r >= 3; r -= 4) init_range(r, lane, hasA, hasB, rankB);
        mbar_wait(sb + O_BAR + 8 * B_EP, 0);
        ep = lds1u(sb + O_EP);
        if (sig) STAMP(45);
        if (rankA < 128) {
          mbar_wait(sb + O_BAR + 8 * B_XS, 0);
          if (sig) STAMP(27);
#pragma unroll
          for (int j = 0; j < 10; j++) xr[j] = lds4u(sb + O_XS + (t >> 3) * 1280 + j * 128 + (t & 7) * 16);
          float s0 = 0.f, s1 = 0.f, q0 = 0.f, q1 = 0.f;
#pragma unroll
          for (int j = 0; j < 10; j++) sumsq8(s0, s1, q0, q1, xr[j]);
          s0 += s1; q0 += q1;
#pragma unroll
          for (int o = 1; o < 8; o *= 2) { s0 += __shfl_xor_sync(~0u, s0, o); q0 += __shfl_xor_sync(~0u, q0, o); }
          const float mean = s0 * (1.f / 640.f);
          const float v = fmaxf(fmaf(-mean, mean, q0 * (1.f / 640.f)), 0.f);
          const float r1 = rsqrtf(v + 1e-5f);
          if ((t & 7) == 0) st_tag(P.sm->rowstat + rankA * 16 + (t >> 3), mean, r1, 0.5f * r1 * rsqrtf(v * r1 * r1 + 1e-5f), ep);
        }
        if (lane == 0) mbar_arrive(sb + O_BAR + 8 * B_XSD);
        if (sig) STAMP(10);
        if (hasA) {
          unsigned t0, c;
          asm volatile("mov.u32 %0, %%clock;" : "=r"(t0));
          do { asm volatile("mov.u32 %0, %%clock;" : "=r"(c)); } while (__any_sync(~0u, c - t0 < POLL_LAG + ww * POLL_STEP));
#pragma unroll 1
          for (int it = 0;; it++) {
            float4 r[3];
            bool ok = true;
#pragma unroll
            for (int j = 0; j < 3; j++) r[j] = ld_tag(P.sm->rowstat + min(tb * 80 + min(lane + 32 * j, 79), 2047));
#pragma unroll
            for (int j = 0; j < 3; j++) ok = ok && __float_as_uint(r[j].w) == ep;
            if (__all_sync(~0u, ok)) {
#pragma unroll
              for (int j = 0; j < 3; j++) {
                const int i = lane + 32 * j;
                if (tb * 80 + i >= 2048) r[j].y = r[j].z = 0.f;
                if (i < 80) {
                  sts2f(sb + O_AB1 + i * 8, r[j].z, -r[j].x * r[j].z);
                  sts2f(sb + O_RM + i * 8, r[j].y, -r[j].x * r[j].y);
                }
              }
              break;
            }
            if (it > (1 << 21)) __trap();
          }
          __syncwarp();
          if (lane == 0) {
            uint32_t old;
            asm volatile("atom.acq_rel.cta.shared::cta.exch.b32 %0, [%1], 1;" : "=r"(old) : "r"(sb + O_EP + 4) : "memory");
            if (old == 0) { mbar_arrive(sb + O_BAR + 8 * B_STAT1); STAMP(6); }
          }
          __syncwarp();
        }
      }

      float acc[40], a1[40];
      if (hasB) {
        mbar_wait(sb + O_EMPTY + 8 * 10, 0);
        if (sig) STAMP(11);
        f1_loop<7>(acc, a1, sb, 0, 6, 4, sig, rankB, P);
        mbar_wait(sb + O_FULL + 8 * 23, 0);
        sts1f(sb + O_R1F + t * 4, gather_tagged<1>(P.sm->rowstat + rb * 128 + t, 0, ep).y);
      }
      if (hasA) {
        mbar_wait(sb + O_BAR + 8 * B_X1W, 0);
        uint4 v[10];
#pragma unroll
        for (int j = 0; j < 10; j++) v[j] = lds4u(sb + O_X1S + (j & 1) * 10240 + (j >> 1) * 2048 + t * 16);
#pragma unroll
        for (int j = 0; j < 5; j++) {
          float s0 = 0.f, s1 = 0.f, q0 = 0.f, q1 = 0.f;
          sumsq8(s0, s1, q0, q1, v[2 * j]);
          sumsq8(s0, s1, q0, q1, v[2 * j + 1]);
          s0 += s1; q0 += q1;
          const bool odd = lane & 1;
          float u = (odd ? q0 : s0) + __shfl_xor_sync(~0u, odd ? s0 : q0, 1);
          u += __shfl_xor_sync(~0u, u, 2);
          u += __shfl_xor_sync(~0u, u, 4);
          const float w = __shfl_xor_sync(~0u, u, 1);
          const int tok = tb * 80 + j * 16 + (t >> 3);
          if ((t & 7) == 0 && tok < 2048) st_tag(P.sm->x1part + fb * 2048 + tok, u, w, 0.f, ep);
        }
      }
      if (hasB) {
        mbar_wait(F1C_GATE, 0);
        f1_loop<4>(acc, a1, sb, 6, 10, 3, sig, rankB, P);
        if (sig) STAMP(12);
        mbar_wait(sb + O_BAR + 8 * B_X1ST, 0);
        bar_sync(3, 128);
        const uint32_t stg = sb + O_X1S;
        const float r00 = lds1f(sb + O_R1F + (ww * 16 + g) * 4), r01 = lds1f(sb + O_R1F + (ww * 16 + g + 8) * 4);
        const float r10 = lds1f(sb + O_R1F + (64 + ww * 16 + g) * 4), r11 = lds1f(sb + O_R1F + (64 + ww * 16 + g + 8) * 4);
#pragma unroll
        for (int i = 0; i < 10; i += 2) {
          stsm_t(stg + tr_off + i * 1024, pack(acc[4 * i] * r00, acc[4 * i + 1] * r00), pack(acc[4 * i + 2] * r01, acc[4 * i + 3] * r01),
                 pack(acc[4 * i + 4] * r00, acc[4 * i + 5] * r00), pack(acc[4 * i + 6] * r01, acc[4 * i + 7] * r01));
          stsm_t(stg + 10240 + tr_off + i * 1024, pack(a1[4 * i] * r10, a1[4 * i + 1] * r10), pack(a1[4 * i + 2] * r11, a1[4 * i + 3] * r11),
                 pack(a1[4 * i + 4] * r10, a1[4 * i + 5] * r10), pack(a1[4 * i + 6] * r11, a1[4 * i + 7] * r11));
        }
        tile_written(sb + O_BAR + 8 * B_UW, lane);
      }
    } else {
      if (warp < 3) init_range(warp, lane, hasA, hasB, rankB);
      if (warp < 7) {
        sts4u(sb + warp * G1SLOT + SLOT + lane * 32, 0x3F803F80u, 0x3F803F80u, 0x3F803F80u, 0x3F803F80u);
        sts4u(sb + warp * G1SLOT + SLOT + lane * 32 + 16, 0x3F803F80u, 0x3F803F80u, 0x3F803F80u, 0x3F803F80u);
        fence_async_smem();
      }
      __syncwarp();
      if (tid == 0) STAMP(41);
      bar_sync(0, 512);
    }
    if (wg < 2 && !hasA) {
      unsigned t0;
      asm volatile("mov.u32 %0, %%clock;" : "=r"(t0));
      t0 += SP_START - 1500 + warp * (SP_GAP / 8);
#pragma unroll 1
      for (int j = 0; j < 43; j++, t0 += SP_GAP) {
        const int i = (j * 16 + (rankA - 130) * 8 + warp) * 32 + lane;
        unsigned c;
        do { asm volatile("mov.u32 %0, %%clock;" : "=r"(c)); } while (__any_sync(~0u, (int)(c - t0) < 0));
        l2_prefetch(i < 15360 ? (const char*)P.w4 + i * 128 : i < 21760 ? (const char*)(P.dft + 640 * 640) + (i - 15360) * 128 : P.fft + (i - 21760) * 128);
      }
    }
    if (wg < 2 && hasA) {
      uint32_t x4[5][4];
      {
        const int half = wg * 2 + (ww >> 1);
        float c1[44];
        uint32_t slot = 0;
        if (tid == 0) STAMP(46);
        if (G1_HOLD) mbar_wait(sb + O_BAR + 8 * B_XSD, 0);
#pragma unroll 1
        for (int st = 0; st < 10; st++) {
          mbar_wait(sb + O_FULL + 8 * st, 0);
          if (tid == 0) STAMP2(0, st);
          uint32_t base = sb + slot * G1SLOT;
          Desc da = desc(base + wg * 8192, 8192), db = desc(base + 16384, 16);
          wg_fence();
#pragma unroll
          for (int k = 0; k < 4; k++) wgmma_ss88<1, 0>(c1, da + k * 128, db + k * 2, (st | k) != 0);
          wg_commit();
          wg_wait<1>();
          if (st && sig) mbar_arrive(sb + O_EMPTY + 8 * (st - 1));
          slot = next_slot<-1, 7>(slot);
        }
        wg_wait<0>();
        if (sig) mbar_arrive(sb + O_EMPTY + 8 * 9);
        if (tid == 0) STAMP(30);
        mbar_wait(sb + O_FULL + 8 * 32, 0);
#pragma unroll
        for (int i = 0; i < 5; i++) ldsm_t(sb + O_XT + wg * 10240 + tr_off + i * 2048, x4[i]);
        bar_sync(6, 256);
        mbar_wait(sb + O_BAR + 8 * B_STAT1, 0);
        if (tid == 0) STAMP(62);
        const uint32_t so = sb + O_STG + half * 5120 + (lane >> 4) * 512 + (lane & 7) * 64 + (((2 * (ww & 1) + ((lane >> 3) & 1)) ^ ((lane >> 1) & 3)) << 4);
#pragma unroll
        for (int i = 0; i < 10; i++) {
          const float4 ab = lds4f(sb + O_AB1 + (i * 8 + 2 * q) * 8);
          float* a = c1 + 4 * i;
          a[0] = fmaf(a[0], ab.x, ab.y * c1[40]); a[1] = fmaf(a[1], ab.z, ab.w * c1[40]);
          a[2] = fmaf(a[2], ab.x, ab.y * c1[42]); a[3] = fmaf(a[3], ab.z, ab.w * c1[42]);
        }
        uint32_t hp[20];
#pragma unroll
        for (int i = 0; i < 12; i++) hp[i] = pack(gelu_half(c1[2 * i]), gelu_half(c1[2 * i + 1]));
#pragma unroll
        for (int i = 0; i < 3; i++) stsm_t(so + i * 1024, hp[4 * i], hp[4 * i + 1], hp[4 * i + 2], hp[4 * i + 3]);
#pragma unroll
        for (int i = 12; i < 16; i++) hp[i] = pack(gelu_half(c1[2 * i]), gelu_half(c1[2 * i + 1]));
        tile_written(sb + O_BAR + 8 * B_HW, lane);
#pragma unroll
        for (int i = 16; i < 20; i++) hp[i] = pack(gelu_half(c1[2 * i]), gelu_half(c1[2 * i + 1]));
#pragma unroll
        for (int i = 3; i < 5; i++) stsm_t(so + i * 1024, hp[4 * i], hp[4 * i + 1], hp[4 * i + 2], hp[4 * i + 3]);
        tile_written(sb + O_BAR + 8 * (B_HW + 1), lane);
        if (tid == 0) STAMP(60);
      }
      if (wg == 1 && task < 120) {
        mbar_wait(sb + O_BAR + 8 * B_W4LD, 0);
        uint32_t r[8][4];
#pragma unroll
        for (int j = 0; j < 8; j++)
          ldsm_t(sb + O_W4B + (ww >> 1) * 8192 + ((j & 1) * 32 + lane) * 128 + ((((ww & 1) * 4 + (j >> 1)) ^ (lane & 7)) << 4), r[j]);
        bar_sync(2, 128);
#pragma unroll
        for (int j = 0; j < 8; j++)
          stsm(sb + O_W4B + (ww * 32 + (j >> 1) * 8 + (lane & 7)) * 128 + ((((j & 1) * 4 + (lane >> 3)) ^ (lane & 7)) << 4),
               r[j][0], r[j][1], r[j][2], r[j][3]);
        tile_written(sb + O_BAR + 8 * B_W4W, lane);
      }
      float acc[40];
#pragma unroll
      for (int i = 0; i < 10; i++) {
        const float4 rm = lds4f(sb + O_RM + (i * 8 + 2 * q) * 8);
        const uint32_t u0 = x4[i >> 1][2 * (i & 1)], u1 = x4[i >> 1][2 * (i & 1) + 1];
        acc[4 * i] = fmaf(blo(u0), rm.x, rm.y); acc[4 * i + 1] = fmaf(bhi(u0), rm.z, rm.w);
        acc[4 * i + 2] = fmaf(blo(u1), rm.x, rm.y); acc[4 * i + 3] = fmaf(bhi(u1), rm.z, rm.w);
      }
      gemm80_loop<1, 3, 7, true, true, true>(acc, sb, 22, 3, 10, wg, sig, rankB, P);
      if (tid == 0) STAMP(32);
      mbar_wait(sb + O_EMPTY + 8 * 31, 0);
#pragma unroll
      for (int i = 0; i < 5; i++)
        stsm_t(sb + O_X1S + wg * 10240 + tr_off + i * 2048, pack(acc[8 * i], acc[8 * i + 1]), pack(acc[8 * i + 2], acc[8 * i + 3]),
               pack(acc[8 * i + 4], acc[8 * i + 5]), pack(acc[8 * i + 6], acc[8 * i + 7]));
      tile_written(sb + O_BAR + 8 * B_X1W, lane);
      if (tid == 0) STAMP(61);
    }

    if (wg == 2) {
      if (hasB) {
          mbar_wait(sb + O_BAR + 8 * B_WLD, 0);
          const uint32_t wa = sb + O_WORK + ((lane >> 3) & 1) * 10752 + ((ww & 1) * 16 + (lane >> 4) * 8 + (lane & 7)) * 336 + (ww >> 1) * 16;
          uint32_t r[11][4];
#pragma unroll
          for (int j = 0; j < 11; j++) ldsm_t(wa + j * 32, r[j]);
          bar_sync(3, 128);
          const uint32_t wo = sb + O_WORK + ((ww >> 1) * 8 + g) * 128 + ((((ww & 1) * 4 + q) ^ g) << 4);
#pragma unroll
          for (int j = 0; j < 11; j++) sts4u(wo + j * 2048, r[j][0], r[j][1], r[j][2], r[j][3]);
          tile_written(sb + O_BAR + 8 * B_WTW, lane);
          if (sig) STAMP(29);
      }
      if (!hasB) {
        mbar_wait(sb + O_BAR + 8 * B_XSD, 0);
        mbar_wait(sb + O_EMPTY + 8 * 31, 0);
        if (sig) { mbar_arrive(sb + O_EMPTY + 8 * 39); mbar_arrive(sb + O_EMPTY + 8 * 40); }
      }
      if (task < 120) {
        mbar_wait(sb + O_FULL + 8 * 33, 0);
        const float2 cs = colsum_warp(P.w3 + ((task % 5) * 128 + ww * 32) * 1536 + (task / 5) * 64, 1536, 1, lane);
        sts2f(sb + O_RED + ww * 256 + ((lane & 7) * 4 + (lane >> 3)) * 8, cs.x, cs.y);
        bar_sync(3, 128);
        if (ww == 0) {
          const float2 a = lds2f(sb + O_RED + lane * 8), b = lds2f(sb + O_RED + 256 + lane * 8);
          const float2 c = lds2f(sb + O_RED + 512 + lane * 8), d = lds2f(sb + O_RED + 768 + lane * 8);
          st_tag(P.sm->cs3 + (task % 5) * 768 + (task / 5) * 32 + lane, (a.x + b.x) + (c.x + d.x), (a.y + b.y) + (c.y + d.y), 0.f, ep);
        }
        if (sig) STAMP(14);
      }
      if (hasB) {
        const float4 p = gather_tagged<5>(P.sm->x1part + rb * 128 + t, 2048, ep);
        const float4 cs = gather_tagged<5>(P.sm->cs3 + cb * 96 + min(t, 95), 768, ep);
        const float m = p.x * (1.f / 640.f);
        sts2f(sb + O_AB3 + t * 8, rsqrtf(fmaxf(fmaf(-m, m, p.y * (1.f / 640.f)), 0.f) + 1e-5f), -m);
        if (t < 96) sts2f(sb + O_CS3 + t * 8, cs.x, cs.y);
        mbar_arrive(sb + O_BAR + 8 * B_STAT3);
        if (sig) STAMP(8);
      }
      mbar_wait(sb + O_BAR + 8 * B_WOK, 0);
#pragma unroll
      for (int i = 0; i < 4; i++) {
        const uint4 u = __ldcg((const uint4*)P.Wt + ((col ? col : 320) + 8) * (WT_LD / 4) + (t >> 2) * 16 + i * 4 + q);
        wf[4 * i] = u.x; wf[4 * i + 1] = u.y; wf[4 * i + 2] = u.z; wf[4 * i + 3] = u.w;
      }
      if (hasB) mbar_wait(sb + O_BAR + 8 * (B_H2W + FFT2_GATE), 0);
    } else if (hasB) {
      {
        float c3[96];
#pragma unroll 1
        for (int st = 0; st < 10; st++) {
          mbar_wait(sb + O_FULL + 8 * (33 + st), 0);
          if (tid == 0 && st == 0) STAMP(34);
          if (tid == 0) STAMP2(0, 33 + st);
          uint32_t base = sb + ((st + 3) & 3) * QSLOT;
          Desc da = desc(base + wg * 8192, 16), db = desc(base + 16384, 8192);
          wg_fence();
#pragma unroll
          for (int k = 0; k < 4; k++) wgmma_ss192<0, 1>(c3, da + k * 2, db + k * 128, (st | k) != 0);
          wg_commit();
          wg_wait<1>();
          if (st && sig) mbar_arrive(sb + O_EMPTY + 8 * (32 + st));
        }
        mbar_wait(sb + O_BAR + 8 * B_STAT3, 0);
        mbar_wait(sb + O_EMPTY + 8 * 85, 0);
        const uint32_t so = sb + O_STG3 + (warp * 16 + (lane & 15)) * 128;
        const float2 ab0 = lds2f(sb + O_AB3 + (warp * 16 + g) * 8), ab1 = lds2f(sb + O_AB3 + (warp * 16 + g + 8) * 8);
        wg_wait<0>();
        if (sig) mbar_arrive(sb + O_EMPTY + 8 * 42);
        if (tid == 0) STAMP(35);
        if (t == 0) STAMP2(3, 7 + wg * 8);
        rs0 = ab0.x; rs1 = ab1.x;
        const float k10 = rs0 * 0.7978845608f, k30 = k10 * rs0 * rs0 * 0.044715f;
        const float k11 = rs1 * 0.7978845608f, k31 = k11 * rs1 * rs1 * 0.044715f;
        float2 cs[4];
#pragma unroll
        for (int i = 0; i < 4; i++) cs[i] = lds2f(sb + O_CS3 + (i * 8 + 2 * q) * 4);
#pragma unroll
        for (int hs = 0; hs < 6; hs++) {
          uint32_t hp[8];
          float2 cn[4];
          if (hs < 5) {
#pragma unroll
            for (int i = 0; i < 4; i++) cn[i] = lds2f(sb + O_CS3 + (((hs + 1) * 4 + i) * 8 + 2 * q) * 4);
          }
#pragma unroll
          for (int i = 0; i < 8; i++) {
            const float mm = (i & 1) ? ab1.y : ab0.y, k1 = (i & 1) ? k11 : k10, k3 = (i & 1) ? k31 : k30;
            const float y0 = fmaf(mm, cs[i >> 1].x, c3[16 * hs + 2 * i]), y1 = fmaf(mm, cs[i >> 1].y, c3[16 * hs + 2 * i + 1]);
            hp[i] = pack(fmaf(y0, tanh_fast(y0 * fmaf(y0 * y0, k3, k1)), y0), fmaf(y1, tanh_fast(y1 * fmaf(y1 * y1, k3, k1)), y1));
          }
          if (hs == 4) tile_written(sb + O_BAR + 8 * (B_H2W + 1), lane);
#pragma unroll
          for (int i = 0; i < 2; i++)
            stsm(so + (hs >> 1) * 16384 + ((((hs & 1) * 4 + 2 * i + (lane >> 4)) ^ (lane & 7)) << 4), hp[4 * i], hp[4 * i + 1], hp[4 * i + 2], hp[4 * i + 3]);
          if (hs == 1) tile_written(sb + O_BAR + 8 * (B_H2A + wg), lane);
#pragma unroll
          for (int i = 0; i < 4; i++) cs[i] = cn[i];
        }
        tile_written(sb + O_BAR + 8 * (B_H2W + 2), lane);
        if (tid == 0) STAMP(39);
      }
    }

    if (!hasB) mbar_wait(sb + O_BAR + 8 * B_XSD, 0);
    if (col < 320) {
      const uint32_t fd = sb + O_FD + ci * 8192;
      const uint32_t zoff = fd + (ww * 16 + (lane & 15)) * 128;
      float d[32];
      uint32_t ac[16], as[16];
      mbar_wait(sb + O_FULL + 8 * (82 + ci), 0);
      mbar_wait(sb + O_BAR + 8 * B_MAT, 0);
      if (sig) STAMP(15 + wg);
      {
        const Desc da = desc(sb + O_M32, 16), db = desc(fd, 8192);
        wg_fence();
#pragma unroll
        for (int k = 0; k < 4; k++) wgmma_ss64<0, 1>(d, da + k * 2, db + k * 128, k != 0);
        wg_commit();
        mbar_wait(sb + O_BAR + 8 * B_FAC, 0);
#pragma unroll
        for (int i = 0; i < 4; i++) {
          const uint4 v = lds4u(sb + O_FAC + i * 2048 + t * 16);
          tw[4 * i] = v.x; tw[4 * i + 1] = v.y; tw[4 * i + 2] = v.z; tw[4 * i + 3] = v.w;
          if (wg < 2) {
            const uint4 u = lds4u(sb + O_FAC + ci * 8192 + (t >> 2) * 256 + i * 64 + q * 16);
            wf[4 * i] = u.x; wf[4 * i + 1] = u.y; wf[4 * i + 2] = u.z; wf[4 * i + 3] = u.w;
          }
        }
        wg_wait<0>();
      }
      const Desc dc = desc(sb + O_C, 16);
#define FST(i) if (tid == 0) STAMP2(3, 20 + i)
      FST(0);
      cmul<false>(d, tw, ac, as);
      FST(1);
      dft64<false>(d, ac, as, dc);
      FST(2);
      cmul<true>(d, wf, ac, as);
      FST(3);
      dft64<true>(d, ac, as, dc);
      FST(4);
      cmul<true>(d, tw, ac, as);
#pragma unroll
      for (int i = 0; i < 8; i += 2)
        stsm(zoff + (((i + (lane >> 4)) ^ (lane & 7)) << 4), ac[2 * i], ac[2 * i + 1], ac[2 * i + 2], ac[2 * i + 3]);
      FST(5);
      fence_async_smem();
      bar_sync(1 + wg, 128);
      FST(6);
      {
        const Desc da = desc(sb + O_M32, 8192), db = desc(fd, 8192);
        wg_fence();
#pragma unroll
        for (int k = 0; k < 4; k++) wgmma_ss64<1, 1>(d, da + k * 128, db + k * 128, k != 0);
        wg_commit();
        wg_wait<0>();
      }
      FST(7);
      if (sig) mbar_arrive(sb + O_EMPTY + 8 * 83);
      mbar_wait(sb + O_EMPTY + 8 * 43, 0);
#pragma unroll
      for (int i = 0; i < 8; i += 2)
        stsm(zoff + (O_WORK - O_FD) + (((i + (lane >> 4)) ^ (lane & 7)) << 4), pack(d[4 * i], d[4 * i + 1]), pack(d[4 * i + 2], d[4 * i + 3]),
             pack(d[4 * i + 4], d[4 * i + 5]), pack(d[4 * i + 6], d[4 * i + 7]));
      tile_written(sb + O_BAR + 8 * (B_VW + ci), lane);
      if (sig) STAMP(24 + wg);
    }

    if (wg < 2 && hasB) {
      float sa[40], acc[40];
      gemm80_loop<0, -1, 7, true, false>(acc, sb, 44, 5, 24, wg, sig, rankB, P);
      if (tid == 0) STAMP(37);
      gemm80_loop<1, -1, 7, false, false>(sa, sb, 68, 1, 10, wg, sig, rankB, P);
      mbar_wait(sb + O_FULL + 8 * 79, 0);
      mbar_wait(sb + O_FULL + 8 * 78, 0);
      wg_wait<0>();
      if (tid == 0) STAMP(19);
      rs0 *= 0.25f; rs1 *= 0.25f;
      uint32_t x4[2][3][4], y4[2][3][4];
      const uint32_t sx = sb + 4 * SLOT + (warp * 16 + (lane & 7)) * 160 + (lane >> 3) * 16;
#pragma unroll
      for (int i = 0; i < 6; i++) {
        const uint32_t o = (i / 3) * 1280 + (i % 3 < 2 ? (i % 3) * 64 : 128 - (lane & 16) * 2);
        ldsm(sx + (O_WORK - 4 * SLOT) + o, y4[i / 3][i % 3]);
        ldsm(sx + o, x4[i / 3][i % 3]);
      }
#pragma unroll
      for (int h = 0; h < 2; h++) {
        const float rs = h ? rs1 : rs0;
#pragma unroll
        for (int j = 0; j < 10; j++) {
          const uint32_t y = y4[h][j >> 2][j & 3];
          uint32_t& x = x4[h][j >> 2][j & 3];
          const int e = 4 * j + 2 * h;
          const float h0 = fmaf(acc[e], rs, 0.5f * blo(y)), h1 = fmaf(acc[e + 1], rs, 0.5f * bhi(y));
          const float g0 = fmaf(h0, tanh_fast(h0), h0), g1 = fmaf(h1, tanh_fast(h1), h1);
          x = pack(fmaf(sa[e], g0, blo(x)), fmaf(sa[e + 1], g1, bhi(x)));
        }
        stsm(sx + h * 1280, x4[h][0][0], x4[h][0][1], x4[h][0][2], x4[h][0][3]);
        stsm(sx + h * 1280 + 64, x4[h][1][0], x4[h][1][1], x4[h][1][2], x4[h][1][3]);
        asm volatile("stmatrix.sync.aligned.m8n8.x2.shared.b16 [%0], {%1, %2};" ::"r"(sx + h * 1280 + 128), "r"(x4[h][2][0]), "r"(x4[h][2][1]) : "memory");
        fence_async_smem();
        __syncwarp();
        if (elect()) tma2_st(&P.m[M_OUT], sb + 4 * SLOT + (warp * 2 + h) * 1280, cb * 80, rb * 128 + warp * 16 + h * 8);
        __syncwarp();
      }
      if (elect()) {
        st_commit();
        st_wait_all();
        if (warp == 0) STAMP(38);
      }
    }
  }
}

typedef CUresult (*EncodeFn)(CUtensorMap*, CUtensorMapDataType, cuuint32_t, void*, const cuuint64_t*, const cuuint64_t*,
                             const cuuint32_t*, const cuuint32_t*, CUtensorMapInterleave, CUtensorMapSwizzle,
                             CUtensorMapL2promotion, CUtensorMapFloatOOBfill);

static void make_map(EncodeFn enc, CUtensorMap* m, const void* p, int rank, uint64_t d0, uint64_t d1, uint64_t d2,
                     uint64_t s1, uint64_t s2, uint32_t b0, uint32_t b1, uint32_t b2, int swz) {
  cuuint64_t dims[3] = {d0, d1, d2}, strides[2] = {s1, s2};
  cuuint32_t box[3] = {b0, b1, b2}, es[3] = {1, 1, 1};
  CUtensorMapSwizzle s = swz == 128 ? CU_TENSOR_MAP_SWIZZLE_128B : swz == 64 ? CU_TENSOR_MAP_SWIZZLE_64B : CU_TENSOR_MAP_SWIZZLE_NONE;
  CUresult r = enc(m, CU_TENSOR_MAP_DATA_TYPE_BFLOAT16, rank, const_cast<void*>(p), dims, strides, box, es,
                   CU_TENSOR_MAP_INTERLEAVE_NONE, s, CU_TENSOR_MAP_L2_PROMOTION_L2_128B, CU_TENSOR_MAP_FLOAT_OOB_FILL_NONE);
  (void)r;
}

extern "C" void kernel_launch(void* const* d_in, const int* in_sizes, int n_in, void* d_out, int out_size) {
  (void)in_sizes; (void)n_in; (void)out_size;
  void* fn = nullptr;
  cudaDriverEntryPointQueryResult qr;
  cudaGetDriverEntryPoint("cuTensorMapEncodeTiled", &fn, cudaEnableDefault, &qr);
  EncodeFn enc = (EncodeFn)fn;
  bf16 *sc, *h2, *UV, *T, *Wt, *w4t;
  cudaGetSymbolAddress((void**)&Wt, g_Wt);
  cudaGetSymbolAddress((void**)&w4t, g_w4t);
  cudaGetSymbolAddress((void**)&T, g_dft);
  cudaGetSymbolAddress((void**)&sc, g_sc);
  cudaGetSymbolAddress((void**)&h2, g_h2);
  cudaGetSymbolAddress((void**)&UV, g_UV);
  Params P;
  P.ops = make_ops();
  cudaGetSymbolAddress((void**)&P.sm, g_small);
  cudaGetSymbolAddress((void**)&P.fft, g_fft);
  P.dft = T;
  P.Wt = (const uint32_t*)Wt;
  P.x = (const bf16*)d_in[0]; P.wr = (const bf16*)d_in[1]; P.wi = (const bf16*)d_in[2];
  P.w1 = (const bf16*)d_in[4]; P.w2 = (const bf16*)d_in[5]; P.w3 = (const bf16*)d_in[6]; P.w4 = (const bf16*)d_in[7];
  make_map(enc, &P.m[L_X80], P.x, 3, 64, 2048, 10, 1280, 128, 64, 80, 1, 128);
  make_map(enc, &P.m[L_XT], P.x, 3, 64, 2048, 10, 1280, 128, 64, 80, 2, 128);
  make_map(enc, &P.m[L_X128], P.x, 3, 64, 2048, 10, 1280, 128, 64, 128, 1, 128);
  make_map(enc, &P.m[L_W1], P.w1, 3, 64, 640, 10, 1280, 128, 64, 64, 2, 128);
  make_map(enc, &P.m[L_W2], P.w2, 3, 64, 640, 10, 1280, 128, 64, 64, 2, 128);
  make_map(enc, &P.m[L_W3], P.w3, 3, 64, 640, 24, 3072, 128, 64, 64, 3, 128);
  make_map(enc, &P.m[L_W4], P.w4, 3, 64, 1536, 10, 1280, 128, 64, 64, 2, 128);
  make_map(enc, &P.m[L_SC80], sc, 3, 64, ROW_H + 2048, 10, 1280, 128, 64, 80, 1, 128);
  make_map(enc, &P.m[L_SC128], sc, 3, 64, ROWS_SC, 10, 1280, 128, 64, 128, 1, 128);
  make_map(enc, &P.m[M_X1ST], sc, 3, 64, ROW_X1 + 2048, 10, 1280, 128, 64, 80, 2, 128);
  make_map(enc, &P.m[M_HST], sc, 2, 640, ROW_H + 2048, 1, 1280, 0, 32, 40, 1, 64);
  make_map(enc, &P.m[L_H2], h2, 3, 64, 2048, 24, 3072, 128, 64, 128, 1, 128);
  make_map(enc, &P.m[M_H2H], h2, 3, 64, 2048, 24, 3072, 128, 64, 64, 1, 128);
  make_map(enc, &P.m[L_T], T, 3, 64, 1280, 10, 1280, 128, 64, 80, 1, 128);
  make_map(enc, &P.m[L_V], UV + 640 * 2048, 3, 64, 640, 32, 4096, 128, 64, 64, 2, 128);
  make_map(enc, &P.m[L_U], UV, 3, 64, 64, 640, 128, 8192, 64, 64, 1, 128);
  make_map(enc, &P.m[R_V], UV, 3, 64, 64, 640, 128, 8192, 8, 64, 1, 0);
  make_map(enc, &P.m[M_UST], UV, 2, 2048, 640, 1, 4096, 0, 64, 80, 1, 128);
  make_map(enc, &P.m[M_VST], UV, 3, 64, 64, 640, 128, 8192, 64, 16, 1, 128);
  make_map(enc, &P.m[L_WR], P.wr, 2, 32 * 321, 64, 1, 64 * 321, 0, 168, 32, 1, 0);
  make_map(enc, &P.m[L_WI], P.wi, 2, 32 * 321, 64, 1, 64 * 321, 0, 168, 32, 1, 0);
  make_map(enc, &P.m[M_WT], Wt, 2, 4096, 344, 1, WT_LD * 4, 0, 64, 56, 1, 128);
  make_map(enc, &P.m[R_U], UV, 2, 2048, 640, 1, 4096, 0, 8, 80, 1, 0);
  make_map(enc, &P.m[L_W4T], w4t, 3, 64, 640, 24, 3072, 128, 64, 80, 1, 128);
  make_map(enc, &P.m[M_W4T], w4t, 3, 64, 640, 24, 3072, 128, 64, 16, 1, 128);
  make_map(enc, &P.m[R_WT], Wt, 2, 4096, 344, 1, WT_LD * 4, 0, 8, 168, 1, 0);
  make_map(enc, &P.m[L_XF], P.x, 2, 640, 2048, 1, 1280, 0, 80, 128, 1, 0);
  make_map(enc, &P.m[L_X1F], sc + ROW_X1 * 640, 2, 640, 2048, 1, 1280, 0, 80, 128, 1, 0);
  make_map(enc, &P.m[M_OUT], d_out, 2, 640, 2048, 1, 1280, 0, 80, 8, 1, 0);
  int dev = 0, nsm = 0;
  cudaGetDevice(&dev);
  cudaDeviceGetAttribute(&nsm, cudaDevAttrMultiProcessorCount, dev);
  auto kern = nsm == 132 ? fused_kernel<true> : fused_kernel<false>;
  cudaFuncSetAttribute(kern, cudaFuncAttributeMaxDynamicSharedMemorySize, SMEM_BYTES);
  kern<<<132, 512, SMEM_BYTES>>>(P);
}
```
